```python
import torch

def _softmax(x, axis=-1):
    return torch.softmax(x, dim=axis)
def _gelu(x):
    return torch.nn.functional.gelu(x, approximate="tanh")
def _silu(x):
    return torch.nn.functional.silu(x)
def _sigmoid(x):
    return torch.sigmoid(x)
def _layernorm(x, axis=-1, eps=1e-5):
    m = x.mean(dim=axis, keepdim=True)
    v = x.var(dim=axis, keepdim=True, unbiased=False)
    return (x - m) / torch.sqrt(v + eps)
def _scatter_add(tgt, idx, src, axis=0):
    return tgt.clone().index_add_(axis, idx, src)
def _segment_sum(src, seg, n):
    out = torch.zeros((n,) + src.shape[1:], dtype=src.dtype)
    return out.index_add_(0, seg, src)
def _pad(x, pw):
    flat = tuple(v for pair in reversed(pw) for v in pair)
    return torch.nn.functional.pad(x, flat)

kernel_name = 'parallel_sum__linear_kernel_hedgehog__dense_activation_gelu__prompt'

def setup_inputs():

    _w = (lambda a: (lambda t: t.to(torch.bfloat16) if t.is_floating_point() else t)(torch.as_tensor(a)))
    def _A_setup():
        B, S, D, H = 1, 2048, 512, 32
        Dh = D // H
        return {
            "x": _w((lambda *s: torch.randn(*s, dtype=torch.bfloat16) * 0.05)(B, S, D)),
            "wqkv": _w((lambda *s: torch.randn(*s, dtype=torch.bfloat16) * 0.2)(D, 3 * D)),
            "w_phi": _w((lambda *s: torch.randn(*s, dtype=torch.bfloat16) * 0.2)(H, Dh, Dh) * (Dh ** -0.5)),
            "wo": _w((lambda *s: torch.randn(*s, dtype=torch.bfloat16) * 0.05)(D, D)),
        }
    _A_in = _A_setup()

    def _B_setup():
        B, S, D, F = 1, 2048, 512, 1376
        return {
            "x": _w((lambda *s: torch.randn(*s, dtype=torch.bfloat16) * 0.05)(B, S, D)),
            "w1": _w((lambda *s: torch.randn(*s, dtype=torch.bfloat16) * 0.8)(D, F) * (D ** -0.5)),
            "b1": _w((lambda *s: torch.randn(*s, dtype=torch.bfloat16) * 12.8)(F) * 0.01),
            "w2": _w((lambda *s: torch.randn(*s, dtype=torch.bfloat16) * 0.4)(F, D) * (F ** -0.5)),
            "b2": _w((lambda *s: torch.randn(*s, dtype=torch.bfloat16) * 6.4)(D) * 0.01),
        }
    _B_in = _B_setup()

    return {
        "A_x": _A_in["x"],
        "A_wqkv": _A_in["wqkv"],
        "A_w_phi": _A_in["w_phi"],
        "A_wo": _A_in["wo"],
        "B_x": _B_in["x"],
        "B_w1": _B_in["w1"],
        "B_b1": _B_in["b1"],
        "B_w2": _B_in["w2"],
        "B_b2": _B_in["b2"],
    }

def reference(A_x, A_wqkv, A_w_phi, A_wo, B_x, B_w1, B_b1, B_w2, B_b2):
    def _A_ref(x, wqkv, w_phi, wo):
        B, S, D = x.shape
        H = 32; Dh = D // H
        qkv = (lambda x, *d: x.permute(*d))((x @ wqkv).reshape(B, S, 3, H, Dh), 2, 0, 3, 1, 4)
        q, k, v = qkv[0], qkv[1], qkv[2]
        pq = torch.einsum("bhsd,hdf->bhsf", q, w_phi)
        pk = torch.einsum("bhsd,hdf->bhsf", k, w_phi)
        phi_q = torch.concatenate([_softmax(pq, axis=-1), _softmax(-pq, axis=-1)], axis=-1)
        phi_k = torch.concatenate([_softmax(pk, axis=-1), _softmax(-pk, axis=-1)], axis=-1)
        kv = torch.einsum("bhsf,bhsd->bhfd", phi_k, v)
        z  = torch.einsum("bhsf->bhf", phi_k)
        num = torch.einsum("bhqf,bhfd->bhqd", phi_q, kv)
        den = torch.einsum("bhqf,bhf->bhq", phi_q, z)[..., None] + 1e-6
        o = num / den
        return (lambda x, *d: x.permute(*d))(o, 0, 2, 1, 3).reshape(B, S, D) @ wo

    def _B_ref(x, w1, b1, w2, b2):
        h = torch.einsum("bsd,df->bsf", x, w1) + b1
        h = _gelu(h)
        return torch.einsum("bsf,fd->bsd", h, w2) + b2

    x = A_x
    xn = _layernorm(x, axis=-1)
    return x + _A_ref(xn, A_wqkv, A_w_phi, A_wo) + _B_ref(xn, B_w1, B_b1, B_w2, B_b2)
```

```cpp
#include <cuda_runtime.h>
#include <cuda_bf16.h>
#include <cuda.h>
#include <stdint.h>

#define X1_AT 1
#define PROMO CU_TENSOR_MAP_L2_PROMOTION_L2_128B
#define MAPPING 2
#define PPB_STAGE 7
#define SPLIT0 1
#define PREFETCH 1
#define PROF_P0 3
#define PROF_P1 4
#define TA_AT 3
#define PP_STAGE 7
#define NORM_PACKED 1

namespace {

constexpr uint32_t SMEM_BASE = 1024;
constexpr int NST = 8;
constexpr int STB = 16384;
constexpr int OFF_INC = NST * STB;
constexpr int OFF_XRES = OFF_INC + 65536;
constexpr int OFF_WBIG = OFF_XRES + 16384;
constexpr int OFF_ONES = OFF_WBIG + 8192;
constexpr int OFF_KVB = OFF_ONES + 1024;
constexpr int OFF_B1 = OFF_KVB + 8704;
constexpr int OFF_B2 = OFF_B1 + 384;
constexpr int OFF_EP = OFF_B2 + 128;
constexpr int OFF_BAR = OFF_EP + 16;
enum { B_XFULL = 0, B_FULL = 8, B_RXA = 16, B_RXB = 18, B_RXC = 20, B_RXFREE = 22, B_MISC = 24, B_XRES = 25, B_KVRAW = 26, B_RXFREE2 = 27, B_FULLB = 29, B_TILE = 31,
       B_EMPTY = 35, B_DONE = 43, B_XFREE = 44, B_KVST = 46, B_PBDONE = 48, B_KVRDY = 49, B_NUM = 50 };
constexpr int SMEM_BYTES = OFF_BAR + B_NUM * 8;
static_assert(SMEM_BYTES <= 232448, "smem");
constexpr int R_KVP = 24576;
constexpr int R_V = 16384;
constexpr int KV_FLOATS = 2176;

__device__ __align__(128) float g_kv[2][8][KV_FLOATS];
__device__ unsigned g_cnt[2][8][32];
__device__ unsigned g_epoch;
__device__ uint4 g_flag[128][8];
__device__ uint4 g_part[128 * 6 * 512];
#define TS(i)
#define TP(i)
#define TSS(p, s)
#define TSW(w, i)
#define TSDUMP()
#define TG(i)
#define LAUNCH_SMEM SMEM_BYTES

struct Params {
    CUtensorMap x, kv, q, w1a, w1b, w2, wo, out, xr;
    const __nv_bfloat16* wphi;
    const __nv_bfloat16* b1;
    const __nv_bfloat16* b2;
    uint8_t role[64];
};

__device__ __forceinline__ void mbar_init(uint32_t bar, uint32_t cnt) { asm volatile("mbarrier.init.shared::cta.b64 [%0], %1;" :: "r"(bar), "r"(cnt) : "memory"); }
__device__ __forceinline__ void mbar_expect_tx(uint32_t bar, uint32_t bytes) { asm volatile("mbarrier.arrive.expect_tx.shared::cta.b64 _, [%0], %1;" :: "r"(bar), "r"(bytes) : "memory"); }
__device__ __forceinline__ void mbar_arrive(uint32_t bar) { asm volatile("mbarrier.arrive.shared::cta.b64 _, [%0];" :: "r"(bar) : "memory"); }
__device__ __forceinline__ void mbar_wait(uint32_t bar, uint32_t parity) {
    asm volatile("{\n"
        ".reg .pred p;\n"
        "WL%=:\n"
        "mbarrier.try_wait.parity.shared::cta.b64 p, [%0], %1;\n"
        "@!p bra WL%=;\n"
        "}" :: "r"(bar), "r"(parity) : "memory");
}
__device__ __forceinline__ void mbar_wait_cluster(uint32_t bar, uint32_t parity) {
    asm volatile("{\n"
        ".reg .pred p;\n"
        "WL%=:\n"
        "mbarrier.try_wait.parity.acquire.cluster.shared::cta.b64 p, [%0], %1;\n"
        "@!p bra WL%=;\n"
        "}" :: "r"(bar), "r"(parity) : "memory");
}
__device__ __forceinline__ void tma3d(uint32_t dst, const CUtensorMap* tm, int c0, int c1, int c2, uint32_t bar) {
    asm volatile("cp.async.bulk.tensor.3d.shared::cluster.global.mbarrier::complete_tx::bytes [%0], [%1, {%3, %4, %5}], [%2];"
        :: "r"(dst), "l"(tm), "r"(bar), "r"(c0), "r"(c1), "r"(c2) : "memory");
}
__device__ __forceinline__ void pf3d(const CUtensorMap* tm, int c0, int c1, int c2) {
    asm volatile("cp.async.bulk.prefetch.tensor.3d.L2.global [%0, {%1, %2, %3}];" :: "l"(tm), "r"(c0), "r"(c1), "r"(c2) : "memory");
}
__device__ __forceinline__ bool elect_one() {
    uint32_t p;
    asm volatile("{ .reg .pred P; elect.sync _|P, 0xffffffff; selp.u32 %0, 1, 0, P; }" : "=r"(p));
    return p;
}
__device__ __forceinline__ void wg_fence() { asm volatile("wgmma.fence.sync.aligned;" ::: "memory"); }
__device__ __forceinline__ void wg_commit() { asm volatile("wgmma.commit_group.sync.aligned;" ::: "memory"); }
template <int N> __device__ __forceinline__ void wg_wait() { asm volatile("wgmma.wait_group.sync.aligned %0;" :: "n"(N) : "memory"); }
__device__ __forceinline__ void fence_async_smem() { asm volatile("fence.proxy.async.shared::cta;" ::: "memory"); }
__device__ __forceinline__ void bar_sync(int id, int n) { asm volatile("bar.sync %0, %1;" :: "r"(id), "r"(n) : "memory"); }
__device__ __forceinline__ void bar_arrive(int id, int n) { asm volatile("bar.arrive %0, %1;" :: "r"(id), "r"(n) : "memory"); }
__device__ __forceinline__ void ldsm4(uint32_t (&r)[4], uint32_t addr) {
    asm volatile("ldmatrix.sync.aligned.m8n8.x4.shared.b16 {%0,%1,%2,%3}, [%4];" : "=r"(r[0]), "=r"(r[1]), "=r"(r[2]), "=r"(r[3]) : "r"(addr) : "memory");
}
__device__ __forceinline__ void stsm4(uint32_t addr, uint32_t a, uint32_t b, uint32_t c, uint32_t d) {
    asm volatile("stmatrix.sync.aligned.m8n8.x4.shared.b16 [%0], {%1,%2,%3,%4};" :: "r"(addr), "r"(a), "r"(b), "r"(c), "r"(d) : "memory");
}
__device__ __forceinline__ void lds128(uint32_t (&r)[4], uint32_t addr) {
    asm volatile("ld.shared.v4.b32 {%0,%1,%2,%3}, [%4];" : "=r"(r[0]), "=r"(r[1]), "=r"(r[2]), "=r"(r[3]) : "r"(addr) : "memory");
}
__device__ __forceinline__ uint32_t lds32(uint32_t addr) { uint32_t r; asm volatile("ld.shared.b32 %0, [%1];" : "=r"(r) : "r"(addr) : "memory"); return r; }
__device__ __forceinline__ void sts128(uint32_t addr, uint32_t a, uint32_t b, uint32_t c, uint32_t d) {
    asm volatile("st.shared.v4.b32 [%0], {%1,%2,%3,%4};" :: "r"(addr), "r"(a), "r"(b), "r"(c), "r"(d) : "memory");
}
__device__ __forceinline__ void sts32(uint32_t addr, uint32_t a) { asm volatile("st.shared.b32 [%0], %1;" :: "r"(addr), "r"(a) : "memory"); }
__device__ __forceinline__ void st_async4(uint32_t addr, const uint32_t (&v)[4], uint32_t bar) {
    asm volatile("st.async.weak.shared::cluster.mbarrier::complete_tx::bytes.v4.b32 [%0], {%1,%2,%3,%4}, [%5];"
        :: "r"(addr), "r"(v[0]), "r"(v[1]), "r"(v[2]), "r"(v[3]), "r"(bar) : "memory");
}
__device__ __forceinline__ uint32_t mapa(uint32_t addr, uint32_t cta) { uint32_t r; asm("mapa.shared::cluster.u32 %0, %1, %2;" : "=r"(r) : "r"(addr), "r"(cta)); return r; }
__device__ __forceinline__ void mma_ones(float (&d)[4], const uint32_t (&a)[4]) {
    asm("mma.sync.aligned.m16n8k16.row.col.f32.bf16.bf16.f32 {%0,%1,%2,%3}, {%4,%5,%6,%7}, {%8,%8}, {%0,%1,%2,%3};"
        : "+f"(d[0]), "+f"(d[1]), "+f"(d[2]), "+f"(d[3]) : "r"(a[0]), "r"(a[1]), "r"(a[2]), "r"(a[3]), "r"(0x3F803F80u));
}
__device__ __forceinline__ uint32_t add2(uint32_t a, uint32_t b) { uint32_t r; asm("add.rn.bf16x2 %0, %1, %2;" : "=r"(r) : "r"(a), "r"(b)); return r; }
__device__ __forceinline__ uint32_t pack2(float lo, float hi) { uint32_t r; asm("cvt.rn.bf16x2.f32 %0, %1, %2;" : "=r"(r) : "f"(hi), "f"(lo)); return r; }
__device__ __forceinline__ float bflo(uint32_t w) { return __uint_as_float(w << 16); }
__device__ __forceinline__ float bfhi(uint32_t w) { return __uint_as_float(w & 0xffff0000u); }
__device__ __forceinline__ float ex2(float x) { float r; asm("ex2.approx.ftz.f32 %0, %1;" : "=f"(r) : "f"(x)); return r; }
__device__ __forceinline__ float rcp(float x) { float r; asm("rcp.approx.ftz.f32 %0, %1;" : "=f"(r) : "f"(x)); return r; }
__device__ __forceinline__ float rsq(float x) { float r; asm("rsqrt.approx.ftz.f32 %0, %1;" : "=f"(r) : "f"(x)); return r; }
__device__ __forceinline__ uint32_t sub2(uint32_t a, uint32_t b) { uint32_t r; asm("sub.rn.bf16x2 %0, %1, %2;" : "=r"(r) : "r"(a), "r"(b)); return r; }
__device__ __forceinline__ void wgmma_rs128_first(float (&d)[64], const uint32_t (&a)[4], uint64_t db) {
    asm volatile("{ .reg .pred p; setp.ne.b32 p, 0, 0; wgmma.mma_async.sync.aligned.m64n128k16.f32.bf16.bf16 "
        "{%0,%1,%2,%3,%4,%5,%6,%7,%8,%9,%10,%11,%12,%13,%14,%15,%16,%17,%18,%19,%20,%21,%22,%23,%24,%25,%26,%27,%28,%29,%30,%31,%32,%33,%34,%35,%36,%37,%38,%39,%40,%41,%42,%43,%44,%45,%46,%47,%48,%49,%50,%51,%52,%53,%54,%55,%56,%57,%58,%59,%60,%61,%62,%63}, {%64,%65,%66,%67}, %68, p, 1, 1, 1; }"
        : "=f"(d[0]),"=f"(d[1]),"=f"(d[2]),"=f"(d[3]),"=f"(d[4]),"=f"(d[5]),"=f"(d[6]),"=f"(d[7]),"=f"(d[8]),"=f"(d[9]),"=f"(d[10]),"=f"(d[11]),"=f"(d[12]),"=f"(d[13]),"=f"(d[14]),"=f"(d[15]),"=f"(d[16]),"=f"(d[17]),"=f"(d[18]),"=f"(d[19]),"=f"(d[20]),"=f"(d[21]),"=f"(d[22]),"=f"(d[23]),"=f"(d[24]),"=f"(d[25]),"=f"(d[26]),"=f"(d[27]),"=f"(d[28]),"=f"(d[29]),"=f"(d[30]),"=f"(d[31]),"=f"(d[32]),"=f"(d[33]),"=f"(d[34]),"=f"(d[35]),"=f"(d[36]),"=f"(d[37]),"=f"(d[38]),"=f"(d[39]),"=f"(d[40]),"=f"(d[41]),"=f"(d[42]),"=f"(d[43]),"=f"(d[44]),"=f"(d[45]),"=f"(d[46]),"=f"(d[47]),"=f"(d[48]),"=f"(d[49]),"=f"(d[50]),"=f"(d[51]),"=f"(d[52]),"=f"(d[53]),"=f"(d[54]),"=f"(d[55]),"=f"(d[56]),"=f"(d[57]),"=f"(d[58]),"=f"(d[59]),"=f"(d[60]),"=f"(d[61]),"=f"(d[62]),"=f"(d[63])
        : "r"(a[0]), "r"(a[1]), "r"(a[2]), "r"(a[3]), "l"(db));
}
__device__ __forceinline__ void wgmma_rs128(float (&d)[64], const uint32_t (&a)[4], uint64_t db) {
    asm volatile("{ .reg .pred p; setp.ne.b32 p, 1, 0; wgmma.mma_async.sync.aligned.m64n128k16.f32.bf16.bf16 "
        "{%0,%1,%2,%3,%4,%5,%6,%7,%8,%9,%10,%11,%12,%13,%14,%15,%16,%17,%18,%19,%20,%21,%22,%23,%24,%25,%26,%27,%28,%29,%30,%31,%32,%33,%34,%35,%36,%37,%38,%39,%40,%41,%42,%43,%44,%45,%46,%47,%48,%49,%50,%51,%52,%53,%54,%55,%56,%57,%58,%59,%60,%61,%62,%63}, {%64,%65,%66,%67}, %68, p, 1, 1, 1; }"
        : "+f"(d[0]),"+f"(d[1]),"+f"(d[2]),"+f"(d[3]),"+f"(d[4]),"+f"(d[5]),"+f"(d[6]),"+f"(d[7]),"+f"(d[8]),"+f"(d[9]),"+f"(d[10]),"+f"(d[11]),"+f"(d[12]),"+f"(d[13]),"+f"(d[14]),"+f"(d[15]),"+f"(d[16]),"+f"(d[17]),"+f"(d[18]),"+f"(d[19]),"+f"(d[20]),"+f"(d[21]),"+f"(d[22]),"+f"(d[23]),"+f"(d[24]),"+f"(d[25]),"+f"(d[26]),"+f"(d[27]),"+f"(d[28]),"+f"(d[29]),"+f"(d[30]),"+f"(d[31]),"+f"(d[32]),"+f"(d[33]),"+f"(d[34]),"+f"(d[35]),"+f"(d[36]),"+f"(d[37]),"+f"(d[38]),"+f"(d[39]),"+f"(d[40]),"+f"(d[41]),"+f"(d[42]),"+f"(d[43]),"+f"(d[44]),"+f"(d[45]),"+f"(d[46]),"+f"(d[47]),"+f"(d[48]),"+f"(d[49]),"+f"(d[50]),"+f"(d[51]),"+f"(d[52]),"+f"(d[53]),"+f"(d[54]),"+f"(d[55]),"+f"(d[56]),"+f"(d[57]),"+f"(d[58]),"+f"(d[59]),"+f"(d[60]),"+f"(d[61]),"+f"(d[62]),"+f"(d[63])
        : "r"(a[0]), "r"(a[1]), "r"(a[2]), "r"(a[3]), "l"(db));
}
__device__ __forceinline__ void wgmma_rs112_first(float (&d)[56], const uint32_t (&a)[4], uint64_t db) {
    asm volatile("{ .reg .pred p; setp.ne.b32 p, 0, 0; wgmma.mma_async.sync.aligned.m64n112k16.f32.bf16.bf16 "
        "{%0,%1,%2,%3,%4,%5,%6,%7,%8,%9,%10,%11,%12,%13,%14,%15,%16,%17,%18,%19,%20,%21,%22,%23,%24,%25,%26,%27,%28,%29,%30,%31,%32,%33,%34,%35,%36,%37,%38,%39,%40,%41,%42,%43,%44,%45,%46,%47,%48,%49,%50,%51,%52,%53,%54,%55}, {%56,%57,%58,%59}, %60, p, 1, 1, 1; }"
        : "=f"(d[0]),"=f"(d[1]),"=f"(d[2]),"=f"(d[3]),"=f"(d[4]),"=f"(d[5]),"=f"(d[6]),"=f"(d[7]),"=f"(d[8]),"=f"(d[9]),"=f"(d[10]),"=f"(d[11]),"=f"(d[12]),"=f"(d[13]),"=f"(d[14]),"=f"(d[15]),"=f"(d[16]),"=f"(d[17]),"=f"(d[18]),"=f"(d[19]),"=f"(d[20]),"=f"(d[21]),"=f"(d[22]),"=f"(d[23]),"=f"(d[24]),"=f"(d[25]),"=f"(d[26]),"=f"(d[27]),"=f"(d[28]),"=f"(d[29]),"=f"(d[30]),"=f"(d[31]),"=f"(d[32]),"=f"(d[33]),"=f"(d[34]),"=f"(d[35]),"=f"(d[36]),"=f"(d[37]),"=f"(d[38]),"=f"(d[39]),"=f"(d[40]),"=f"(d[41]),"=f"(d[42]),"=f"(d[43]),"=f"(d[44]),"=f"(d[45]),"=f"(d[46]),"=f"(d[47]),"=f"(d[48]),"=f"(d[49]),"=f"(d[50]),"=f"(d[51]),"=f"(d[52]),"=f"(d[53]),"=f"(d[54]),"=f"(d[55])
        : "r"(a[0]), "r"(a[1]), "r"(a[2]), "r"(a[3]), "l"(db));
}
__device__ __forceinline__ void wgmma_rs112(float (&d)[56], const uint32_t (&a)[4], uint64_t db) {
    asm volatile("{ .reg .pred p; setp.ne.b32 p, 1, 0; wgmma.mma_async.sync.aligned.m64n112k16.f32.bf16.bf16 "
        "{%0,%1,%2,%3,%4,%5,%6,%7,%8,%9,%10,%11,%12,%13,%14,%15,%16,%17,%18,%19,%20,%21,%22,%23,%24,%25,%26,%27,%28,%29,%30,%31,%32,%33,%34,%35,%36,%37,%38,%39,%40,%41,%42,%43,%44,%45,%46,%47,%48,%49,%50,%51,%52,%53,%54,%55}, {%56,%57,%58,%59}, %60, p, 1, 1, 1; }"
        : "+f"(d[0]),"+f"(d[1]),"+f"(d[2]),"+f"(d[3]),"+f"(d[4]),"+f"(d[5]),"+f"(d[6]),"+f"(d[7]),"+f"(d[8]),"+f"(d[9]),"+f"(d[10]),"+f"(d[11]),"+f"(d[12]),"+f"(d[13]),"+f"(d[14]),"+f"(d[15]),"+f"(d[16]),"+f"(d[17]),"+f"(d[18]),"+f"(d[19]),"+f"(d[20]),"+f"(d[21]),"+f"(d[22]),"+f"(d[23]),"+f"(d[24]),"+f"(d[25]),"+f"(d[26]),"+f"(d[27]),"+f"(d[28]),"+f"(d[29]),"+f"(d[30]),"+f"(d[31]),"+f"(d[32]),"+f"(d[33]),"+f"(d[34]),"+f"(d[35]),"+f"(d[36]),"+f"(d[37]),"+f"(d[38]),"+f"(d[39]),"+f"(d[40]),"+f"(d[41]),"+f"(d[42]),"+f"(d[43]),"+f"(d[44]),"+f"(d[45]),"+f"(d[46]),"+f"(d[47]),"+f"(d[48]),"+f"(d[49]),"+f"(d[50]),"+f"(d[51]),"+f"(d[52]),"+f"(d[53]),"+f"(d[54]),"+f"(d[55])
        : "r"(a[0]), "r"(a[1]), "r"(a[2]), "r"(a[3]), "l"(db));
}
__device__ __forceinline__ void wgmma_rs64_first(float (&d)[32], const uint32_t (&a)[4], uint64_t db) {
    asm volatile("{ .reg .pred p; setp.ne.b32 p, 0, 0; wgmma.mma_async.sync.aligned.m64n64k16.f32.bf16.bf16 "
        "{%0,%1,%2,%3,%4,%5,%6,%7,%8,%9,%10,%11,%12,%13,%14,%15,%16,%17,%18,%19,%20,%21,%22,%23,%24,%25,%26,%27,%28,%29,%30,%31}, {%32,%33,%34,%35}, %36, p, 1, 1, 1; }"
        : "=f"(d[0]),"=f"(d[1]),"=f"(d[2]),"=f"(d[3]),"=f"(d[4]),"=f"(d[5]),"=f"(d[6]),"=f"(d[7]),"=f"(d[8]),"=f"(d[9]),"=f"(d[10]),"=f"(d[11]),"=f"(d[12]),"=f"(d[13]),"=f"(d[14]),"=f"(d[15]),"=f"(d[16]),"=f"(d[17]),"=f"(d[18]),"=f"(d[19]),"=f"(d[20]),"=f"(d[21]),"=f"(d[22]),"=f"(d[23]),"=f"(d[24]),"=f"(d[25]),"=f"(d[26]),"=f"(d[27]),"=f"(d[28]),"=f"(d[29]),"=f"(d[30]),"=f"(d[31])
        : "r"(a[0]), "r"(a[1]), "r"(a[2]), "r"(a[3]), "l"(db));
}
__device__ __forceinline__ void wgmma_rs64(float (&d)[32], const uint32_t (&a)[4], uint64_t db) {
    asm volatile("{ .reg .pred p; setp.ne.b32 p, 1, 0; wgmma.mma_async.sync.aligned.m64n64k16.f32.bf16.bf16 "
        "{%0,%1,%2,%3,%4,%5,%6,%7,%8,%9,%10,%11,%12,%13,%14,%15,%16,%17,%18,%19,%20,%21,%22,%23,%24,%25,%26,%27,%28,%29,%30,%31}, {%32,%33,%34,%35}, %36, p, 1, 1, 1; }"
        : "+f"(d[0]),"+f"(d[1]),"+f"(d[2]),"+f"(d[3]),"+f"(d[4]),"+f"(d[5]),"+f"(d[6]),"+f"(d[7]),"+f"(d[8]),"+f"(d[9]),"+f"(d[10]),"+f"(d[11]),"+f"(d[12]),"+f"(d[13]),"+f"(d[14]),"+f"(d[15]),"+f"(d[16]),"+f"(d[17]),"+f"(d[18]),"+f"(d[19]),"+f"(d[20]),"+f"(d[21]),"+f"(d[22]),"+f"(d[23]),"+f"(d[24]),"+f"(d[25]),"+f"(d[26]),"+f"(d[27]),"+f"(d[28]),"+f"(d[29]),"+f"(d[30]),"+f"(d[31])
        : "r"(a[0]), "r"(a[1]), "r"(a[2]), "r"(a[3]), "l"(db));
}
template <uint32_t AHI, uint32_t BHI>
__device__ __forceinline__ void wgmma_ss40_first(float (&d)[20], uint32_t alo, uint32_t blo) {
    asm volatile("{ .reg .pred p; .reg .b64 da, db; setp.ne.b32 p, 0, 0; mov.b64 da, {%20, %22}; mov.b64 db, {%21, %23}; "
        "wgmma.mma_async.sync.aligned.m64n40k16.f32.bf16.bf16 "
        "{%0,%1,%2,%3,%4,%5,%6,%7,%8,%9,%10,%11,%12,%13,%14,%15,%16,%17,%18,%19}, da, db, p, 1, 1, 1, 1; }"
        : "=f"(d[0]),"=f"(d[1]),"=f"(d[2]),"=f"(d[3]),"=f"(d[4]),"=f"(d[5]),"=f"(d[6]),"=f"(d[7]),"=f"(d[8]),"=f"(d[9]),"=f"(d[10]),"=f"(d[11]),"=f"(d[12]),"=f"(d[13]),"=f"(d[14]),"=f"(d[15]),"=f"(d[16]),"=f"(d[17]),"=f"(d[18]),"=f"(d[19])
        : "r"(alo), "r"(blo), "n"(AHI), "n"(BHI));
}
template <uint32_t AHI, uint32_t BHI>
__device__ __forceinline__ void wgmma_ss40(float (&d)[20], uint32_t alo, uint32_t blo) {
    asm volatile("{ .reg .pred p; .reg .b64 da, db; setp.ne.b32 p, 1, 0; mov.b64 da, {%20, %22}; mov.b64 db, {%21, %23}; "
        "wgmma.mma_async.sync.aligned.m64n40k16.f32.bf16.bf16 "
        "{%0,%1,%2,%3,%4,%5,%6,%7,%8,%9,%10,%11,%12,%13,%14,%15,%16,%17,%18,%19}, da, db, p, 1, 1, 1, 1; }"
        : "+f"(d[0]),"+f"(d[1]),"+f"(d[2]),"+f"(d[3]),"+f"(d[4]),"+f"(d[5]),"+f"(d[6]),"+f"(d[7]),"+f"(d[8]),"+f"(d[9]),"+f"(d[10]),"+f"(d[11]),"+f"(d[12]),"+f"(d[13]),"+f"(d[14]),"+f"(d[15]),"+f"(d[16]),"+f"(d[17]),"+f"(d[18]),"+f"(d[19])
        : "r"(alo), "r"(blo), "n"(AHI), "n"(BHI));
}
template <uint32_t AHI, uint32_t BHI>
__device__ __forceinline__ void wgmma_ss24_first(float (&d)[12], uint32_t alo, uint32_t blo) {
    asm volatile("{ .reg .pred p; .reg .b64 da, db; setp.ne.b32 p, 0, 0; mov.b64 da, {%12, %14}; mov.b64 db, {%13, %15}; "
        "wgmma.mma_async.sync.aligned.m64n24k16.f32.bf16.bf16 "
        "{%0,%1,%2,%3,%4,%5,%6,%7,%8,%9,%10,%11}, da, db, p, 1, 1, 0, 1; }"
        : "=f"(d[0]),"=f"(d[1]),"=f"(d[2]),"=f"(d[3]),"=f"(d[4]),"=f"(d[5]),"=f"(d[6]),"=f"(d[7]),"=f"(d[8]),"=f"(d[9]),"=f"(d[10]),"=f"(d[11])
        : "r"(alo), "r"(blo), "n"(AHI), "n"(BHI));
}
template <uint32_t AHI, uint32_t BHI>
__device__ __forceinline__ void wgmma_ss24(float (&d)[12], uint32_t alo, uint32_t blo) {
    asm volatile("{ .reg .pred p; .reg .b64 da, db; setp.ne.b32 p, 1, 0; mov.b64 da, {%12, %14}; mov.b64 db, {%13, %15}; "
        "wgmma.mma_async.sync.aligned.m64n24k16.f32.bf16.bf16 "
        "{%0,%1,%2,%3,%4,%5,%6,%7,%8,%9,%10,%11}, da, db, p, 1, 1, 0, 1; }"
        : "+f"(d[0]),"+f"(d[1]),"+f"(d[2]),"+f"(d[3]),"+f"(d[4]),"+f"(d[5]),"+f"(d[6]),"+f"(d[7]),"+f"(d[8]),"+f"(d[9]),"+f"(d[10]),"+f"(d[11])
        : "r"(alo), "r"(blo), "n"(AHI), "n"(BHI));
}
__device__ __forceinline__ void wgmma_rs64r_first(float (&d)[32], const uint32_t (&a)[4], uint32_t blo) {
    asm volatile("{ .reg .pred p; .reg .b64 db; mov.b64 db, {%36, 0x40000040}; setp.ne.b32 p, 0, 0; wgmma.mma_async.sync.aligned.m64n64k16.f32.bf16.bf16 "
        "{%0,%1,%2,%3,%4,%5,%6,%7,%8,%9,%10,%11,%12,%13,%14,%15,%16,%17,%18,%19,%20,%21,%22,%23,%24,%25,%26,%27,%28,%29,%30,%31}, {%32,%33,%34,%35}, db, p, 1, 1, 1; }"
        : "=f"(d[0]),"=f"(d[1]),"=f"(d[2]),"=f"(d[3]),"=f"(d[4]),"=f"(d[5]),"=f"(d[6]),"=f"(d[7]),"=f"(d[8]),"=f"(d[9]),"=f"(d[10]),"=f"(d[11]),"=f"(d[12]),"=f"(d[13]),"=f"(d[14]),"=f"(d[15]),"=f"(d[16]),"=f"(d[17]),"=f"(d[18]),"=f"(d[19]),"=f"(d[20]),"=f"(d[21]),"=f"(d[22]),"=f"(d[23]),"=f"(d[24]),"=f"(d[25]),"=f"(d[26]),"=f"(d[27]),"=f"(d[28]),"=f"(d[29]),"=f"(d[30]),"=f"(d[31])
        : "r"(a[0]), "r"(a[1]), "r"(a[2]), "r"(a[3]), "r"(blo));
}
__device__ __forceinline__ void wgmma_rs64r(float (&d)[32], const uint32_t (&a)[4], uint32_t blo) {
    asm volatile("{ .reg .pred p; .reg .b64 db; mov.b64 db, {%36, 0x40000040}; setp.ne.b32 p, 1, 0; wgmma.mma_async.sync.aligned.m64n64k16.f32.bf16.bf16 "
        "{%0,%1,%2,%3,%4,%5,%6,%7,%8,%9,%10,%11,%12,%13,%14,%15,%16,%17,%18,%19,%20,%21,%22,%23,%24,%25,%26,%27,%28,%29,%30,%31}, {%32,%33,%34,%35}, db, p, 1, 1, 1; }"
        : "+f"(d[0]),"+f"(d[1]),"+f"(d[2]),"+f"(d[3]),"+f"(d[4]),"+f"(d[5]),"+f"(d[6]),"+f"(d[7]),"+f"(d[8]),"+f"(d[9]),"+f"(d[10]),"+f"(d[11]),"+f"(d[12]),"+f"(d[13]),"+f"(d[14]),"+f"(d[15]),"+f"(d[16]),"+f"(d[17]),"+f"(d[18]),"+f"(d[19]),"+f"(d[20]),"+f"(d[21]),"+f"(d[22]),"+f"(d[23]),"+f"(d[24]),"+f"(d[25]),"+f"(d[26]),"+f"(d[27]),"+f"(d[28]),"+f"(d[29]),"+f"(d[30]),"+f"(d[31])
        : "r"(a[0]), "r"(a[1]), "r"(a[2]), "r"(a[3]), "r"(blo));
}

constexpr uint32_t ONES2 = 0x3F803F80u;

__device__ __forceinline__ uint32_t fma2(uint32_t a, uint32_t b, uint32_t c) { uint32_t r; asm("fma.rn.bf16x2 %0, %1, %2, %3;" : "=r"(r) : "r"(a), "r"(b), "r"(c)); return r; }
__device__ __forceinline__ uint32_t mul2(uint32_t a, uint32_t b) { uint32_t r; asm("mul.rn.bf16x2 %0, %1, %2;" : "=r"(r) : "r"(a), "r"(b)); return r; }
__device__ __forceinline__ uint32_t never(float a, float b) { return (__float_as_uint(a) & __float_as_uint(b)) == 0xFFFFFFFFu; }
__device__ __forceinline__ void norm4(uint32_t (*A)[4], uint32_t s0, uint32_t s1, uint32_t o0, uint32_t o1) {
    #pragma unroll
    for (int k = 0; k < 4; k++) { A[k][0] = fma2(A[k][0], s0, o0); A[k][1] = fma2(A[k][1], s1, o1); A[k][2] = fma2(A[k][2], s0, o0); A[k][3] = fma2(A[k][3], s1, o1); }
}
__device__ __forceinline__ void sum8(const uint32_t (*A)[4], float& s0, float& s1) {
    uint32_t c[8];
    #pragma unroll
    for (int i = 0; i < 8; i++) c[i] = add2(add2(A[i & 4][i & 3], A[(i & 4) + 1][i & 3]), add2(A[(i & 4) + 2][i & 3], A[(i & 4) + 3][i & 3]));
    #pragma unroll
    for (int i = 0; i < 4; i++) c[i] = add2(c[i], c[i + 4]);
    s0 += (bflo(c[0]) + bfhi(c[0])) + (bflo(c[2]) + bfhi(c[2]));
    s1 += (bflo(c[1]) + bfhi(c[1])) + (bflo(c[3]) + bfhi(c[3]));
}
__device__ __forceinline__ void sumsq8(const uint32_t (*A)[4], float& q0, float& q1) {
    uint32_t c[4];
    #pragma unroll
    for (int k = 0; k < 8; k++) {
        #pragma unroll
        for (int i = 0; i < 4; i++) c[i] = k ? fma2(A[k][i], A[k][i], c[i]) : mul2(A[k][i], A[k][i]);
    }
    q0 += (bflo(c[0]) + bfhi(c[0])) + (bflo(c[2]) + bfhi(c[2]));
    q1 += (bflo(c[1]) + bfhi(c[1])) + (bflo(c[3]) + bfhi(c[3]));
}
__host__ __device__ constexpr uint64_t desc_hi(uint32_t lbo, uint32_t sbo, uint32_t swz) { return ((uint64_t)(lbo >> 4) << 16) | ((uint64_t)(sbo >> 4) << 32) | ((uint64_t)swz << 62); }

__device__ __forceinline__ void logits_issue(const float* acc, uint32_t (&a)[4][4], float (&p)[32]) {
    constexpr uint64_t dW = (uint64_t)((SMEM_BASE + OFF_WBIG) >> 4) | desc_hi(8192, 1024, 1);
    #pragma unroll
    for (int h = 0; h < 4; h++) {
        const float* k = acc + 8 * h;
        a[h][0] = pack2(k[0], k[1]); a[h][1] = pack2(k[2], k[3]); a[h][2] = pack2(k[4], k[5]); a[h][3] = pack2(k[6], k[7]);
    }
    wg_fence();
    #pragma unroll
    for (int h = 0; h < 4; h++) { if (h == 0) wgmma_rs64_first(p, a[0], dW); else wgmma_rs64(p, a[h], dW + h * 128); }
    wg_commit();
}
__device__ __forceinline__ void kv_mma(float (&kv0)[20], float (&kv1)[20], uint32_t wg) {
    constexpr uint32_t base = SMEM_BASE + OFF_INC, AHI = (uint32_t)(desc_hi(0, 1024, 1) >> 32), BHI = (uint32_t)(desc_hi(0, 512, 2) >> 32);
    const uint32_t oa = wg * 2048, ob = wg * (2048u - (2048u << 16));
    #pragma unroll
    for (int hp = 0; hp < 2; hp++) {
        #pragma unroll
        for (int ks = 0; ks < 4; ks++) {
            const uint32_t vb = base + R_V + hp * 4096 + ks * 1024;
            const uint32_t a = oa + (((base + hp * 8192 + ks * 2048) >> 4) | (512u << 16));
            const uint32_t b = ob + ((vb >> 4) | (((SMEM_BASE + OFF_ONES - vb) >> 4) << 16));
            if (hp == 0) { if (ks == 0) wgmma_ss40_first<AHI, BHI>(kv0, a, b); else wgmma_ss40<AHI, BHI>(kv0, a, b); }
            else { if (ks == 0) wgmma_ss40_first<AHI, BHI>(kv1, a, b); else wgmma_ss40<AHI, BHI>(kv1, a, b); }
        }
        wg_commit();
    }
}
__device__ __forceinline__ void readout_mma(float (&o)[4][12], uint32_t wg) {
    constexpr uint32_t base = SMEM_BASE + OFF_INC, AHI = (uint32_t)(desc_hi(0, 1024, 1) >> 32), BHI = (uint32_t)(desc_hi(0, 256, 0) >> 32);
    const uint32_t oa = wg * 2048;
    #pragma unroll
    for (int h = 0; h < 4; h++) {
        #pragma unroll
        for (int sg = 0; sg < 2; sg++) {
            const uint32_t a = oa + (((base + (h >> 1) * 8192 + 32 * ((2 * (h & 1) + sg) ^ (h >> 1))) >> 4) | (1u << 16));
            const uint32_t b = ((SMEM_BASE + OFF_KVB + h * 2048 + sg * 768) >> 4) | (8u << 16);
            if (sg == 0) wgmma_ss24_first<AHI, BHI>(o[h], a, b); else wgmma_ss24<AHI, BHI>(o[h], a, b);
        }
    }
}
__device__ __forceinline__ void features(const float (&p)[32], uint32_t addr) {
    float rs[4];
    #pragma unroll
    for (int q = 0; q < 4; q++) {
        const int r = q >> 1, sg = q & 1;
        float m[8];
        #pragma unroll
        for (int i = 0; i < 8; i++) m[i] = sg ? fminf(p[4 * i + 2 * r], p[4 * i + 2 * r + 1]) : fmaxf(p[4 * i + 2 * r], p[4 * i + 2 * r + 1]);
        #pragma unroll
        for (int o = 4; o > 0; o >>= 1) {
            #pragma unroll
            for (int i = 0; i < o; i++) m[i] = sg ? fminf(m[i], m[i + o]) : fmaxf(m[i], m[i + o]);
        }
        const float c = sg ? -1.4426950408889634f : 1.4426950408889634f;
        float off = m[0] * -c;
        if (q >= 2) off = fmaf(rs[q - 2], 0.f, off);
        float e[16], s[8];
        #pragma unroll
        for (int i = 0; i < 16; i++) e[i] = ex2(fmaf(p[4 * (i >> 1) + 2 * r + (i & 1)], c, off));
        #pragma unroll
        for (int i = 0; i < 8; i++) s[i] = e[2 * i] + e[2 * i + 1];
        rs[q] = rcp(((s[0] + s[1]) + (s[2] + s[3])) + ((s[4] + s[5]) + (s[6] + s[7])));
        uint32_t w[8];
        const uint32_t r2 = pack2(rs[q], rs[q]);
        #pragma unroll
        for (int i = 0; i < 8; i++) w[i] = mul2(pack2(e[2 * i], e[2 * i + 1]), r2);
        sts128((addr ^ (32 * sg)) + 1024 * r, w[0], w[1], w[2], w[3]);
        sts128((addr ^ (32 * sg + 16)) + 1024 * r, w[4], w[5], w[6], w[7]);
    }
}
__device__ __forceinline__ uint32_t gelu2(uint32_t h) {
    uint32_t u = mul2(h, fma2(mul2(h, h), 0x3E923E92u, 0x3FCC3FCCu));
    asm("tanh.approx.bf16x2 %0, %0;" : "+r"(u));
    return fma2(h, u, h);
}
__device__ __forceinline__ void pre_gelu(uint32_t (&o)[4], const float* a, uint32_t ba, uint32_t bb) {
    o[0] = fma2(pack2(a[0], a[1]), 0x3F003F00u, ba); o[1] = fma2(pack2(a[2], a[3]), 0x3F003F00u, ba);
    o[2] = fma2(pack2(a[4], a[5]), 0x3F003F00u, bb); o[3] = fma2(pack2(a[6], a[7]), 0x3F003F00u, bb);
}
__device__ __forceinline__ void gelu4(uint32_t (&o)[4]) { o[0] = gelu2(o[0]); o[1] = gelu2(o[1]); o[2] = gelu2(o[2]); o[3] = gelu2(o[3]); }
__device__ __forceinline__ void release(uint32_t sb, int s, int lane) {
    if (lane == 0) mbar_arrive(sb + OFF_BAR + (B_EMPTY + s) * 8);
}
__device__ __forceinline__ void wait_full(uint32_t sb, int s, int parity) { mbar_wait(sb + OFF_BAR + (B_FULL + s) * 8, parity); }

__device__ __forceinline__ void store_kv(const float (&kv)[20], uint32_t o, uint32_t zo, bool hi, int t) {
    #pragma unroll
    for (int nt = 0; nt < 2; nt++)
        sts128(o + nt * 512, __float_as_uint(hi ? kv[8 + 4 * nt] : kv[4 * nt]), __float_as_uint(hi ? kv[9 + 4 * nt] : kv[1 + 4 * nt]),
               __float_as_uint(hi ? kv[10 + 4 * nt] : kv[2 + 4 * nt]), __float_as_uint(hi ? kv[11 + 4 * nt] : kv[3 + 4 * nt]));
    if (t == 0) { sts32(zo, __float_as_uint(kv[16])); sts32(zo + 32, __float_as_uint(kv[18])); }
}
template <int N>
__device__ __forceinline__ void pack_tile(uint32_t (&p)[N][4], const float* acc, uint32_t tag) {
    #pragma unroll
    for (int i = 0; i < N; i++) {
        p[i][0] = (pack2(acc[8 * i + 0], acc[8 * i + 1]) & ~1u) | tag;
        p[i][1] = pack2(acc[8 * i + 2], acc[8 * i + 3]);
        p[i][2] = (pack2(acc[8 * i + 4], acc[8 * i + 5]) & ~1u) | tag;
        p[i][3] = pack2(acc[8 * i + 6], acc[8 * i + 7]);
    }
}
__device__ __forceinline__ void stg128(uint4* dst, const uint32_t (&p)[4]) {
    asm volatile("st.relaxed.gpu.global.v4.b32 [%0], {%1,%2,%3,%4};" :: "l"(dst), "r"(p[0]), "r"(p[1]), "r"(p[2]), "r"(p[3]) : "memory");
}
__device__ __forceinline__ void set_flag(uint4* flag, int w, uint32_t fv, int lane) {
    if (lane == 0) asm volatile("st.relaxed.gpu.global.u32 [%0], %1;" :: "l"((uint32_t*)flag + w), "r"(fv) : "memory");
}
template <int N>
__device__ __forceinline__ void check_tile(uint32_t (&v)[N][4], const uint4* src, uint32_t tag) {
    while (true) {
        uint32_t bad = 0;
        #pragma unroll
        for (int i = 0; i < N; i++) bad |= (v[i][0] ^ tag) | (v[i][2] ^ tag);
        if (!__any_sync(0xffffffffu, bad & 1)) break;
        #pragma unroll
        for (int i = 0; i < N; i++)
            asm volatile("ld.relaxed.gpu.global.v4.b32 {%0,%1,%2,%3}, [%4];" : "=r"(v[i][0]), "=r"(v[i][1]), "=r"(v[i][2]), "=r"(v[i][3]) : "l"(src + i * 128) : "memory");
    }
}

#define MMA_STAGE(SPLIT, BODY)                                                             \
    wg_fence();                                                                            \
    _Pragma("unroll")                                                                      \
    for (int k = 0; k < 4; k++) {                                                          \
        const uint64_t d = dB + (uint64_t)((s * STB + k * 2048) >> 4);                     \
        BODY;                                                                              \
        if (SPLIT && s == 0 && k == 1) wg_commit();                                        \
    }                                                                                      \
    wg_commit()
#define STAGE_WAIT() wg_wait<1>()
#define G2_A(s, k) ((s) < 2 ? Ha[4 * ((s) & 1) + (k)] : (s) < 4 ? Pa[4 * ((s) & 1) + (k)] : (s) < 6 ? Hb[3 * ((s) & 1) + (k)] : Pb[3 * ((s) & 1) + (k)])
#define G2_HAS(s, k) ((k) < 3 || ((s) != 4 && (s) != 6))

__global__ void __cluster_dims__(2, 1, 1) __launch_bounds__(384, 1)
fused_kernel(const __grid_constant__ Params P) {
    extern __shared__ __align__(1024) uint8_t smem_raw[];
    const uint32_t sb = (uint32_t)__cvta_generic_to_shared(smem_raw);
    const int tid = threadIdx.x, warp = tid >> 5, lane = tid & 31;
    const int role = P.role[blockIdx.x >> 1];
    const int m = role >> 2, c = role & 3, r = blockIdx.x & 1, j = 2 * c + r, cc = c >> 1;
    TS(31);
    TG(41);
    const uint32_t bar = sb + OFF_BAR;

    if (warp >= 8) {
        asm volatile("setmaxnreg.dec.sync.aligned.u32 24;");
        if (warp == 8) {
            const bool el = elect_one();
            if (el) {
                #pragma unroll
                for (int i = 0; i < 4; i++) mbar_init(bar + (B_XFULL + i) * 8, 1);
                asm volatile("fence.mbarrier_init.release.cluster;" ::: "memory");
                #pragma unroll
                for (int i = 0; i < 4; i++) {
                    mbar_expect_tx(bar + (B_XFULL + i) * 8, STB);
                    tma3d(sb + (4 + i) * STB, &P.x, 0, m * 128, 2 * i, bar + (B_XFULL + i) * 8);
                }
                TP(43);
                #pragma unroll
                for (int i = 4; i < B_NUM; i++) mbar_init(bar + i * 8, i == B_MISC ? 3 : i < B_EMPTY ? 1 : i < B_XFREE ? 8 : i < B_KVRDY ? 4 : 2);
                #pragma unroll
                for (int i = B_RXA; i < B_RXFREE; i++) mbar_expect_tx(bar + i * 8, i < B_RXB ? 16384 : i < B_RXC ? 6144 : 8192);
                asm volatile("fence.mbarrier_init.release.cluster;" ::: "memory");
                TP(40);
            }
            __syncwarp();
            bar_arrive(0, 384);
            if (el) {
                #pragma unroll 1
                for (int s = 0; s < 4; s++) {
                    if (s == X1_AT) {
                        #pragma unroll 1
                        for (int i = 0; i < 4; i++) {
                            mbar_expect_tx(bar + (B_XFULL + 4 + i) * 8, STB);
                            tma3d(sb + OFF_INC + i * STB, &P.x, 0, m * 128 + 64, 2 * i, bar + (B_XFULL + 4 + i) * 8);
                        }
                    }
                    mbar_expect_tx(bar + (B_FULL + s) * 8, STB);
                    tma3d(sb + s * STB, &P.kv, 64 * j, 64 * s, 1, bar + (B_FULL + s) * 8);
                }
                if (m < 4) pf3d(&P.kv, 64 * j, 256 + 64 * m, 1);
            }
            __syncwarp();
            asm volatile("barrier.cluster.arrive.relaxed.aligned;" ::: "memory");
            if (el) {
                mbar_wait(bar + B_XFREE * 8, 0);
                #pragma unroll 1
                for (int s = 4; s < 8; s++) {
                    mbar_expect_tx(bar + (B_FULL + s) * 8, STB);
                    tma3d(sb + s * STB, &P.kv, 64 * j, 64 * s, 1, bar + (B_FULL + s) * 8);
                }
                if (PREFETCH) {
                    const int s = m & 7, jj = j ^ ((s >> 1) & 1), ch = 4 * r + 2 * (m >> 3);
                    if (m < 8) pf3d(&P.w1a, 176 * j, 64 * s, 0);
                    else { pf3d(&P.q, 64 * j, 64 * s, 0); pf3d(&P.w1b, 176 * j + 128, 64 * s, 0); }
                    mbar_wait(bar + (B_EMPTY + 0) * 8, 0);
                    if (s == 5 || s == 7) pf3d(&P.wo, 0, 64 * jj, ch);
                    else pf3d(&P.w2, 0, 176 * jj + (s < 4 ? 64 * (s & 1) : 128), ch);
                }
                #pragma unroll 1
                for (int s = 0; s < 8; s++) {
                    mbar_wait(bar + (B_EMPTY + s) * 8, 0);
                    mbar_expect_tx(bar + (B_FULL + s) * 8, STB);
                    tma3d(sb + s * STB, &P.w1a, 176 * j, 64 * s, 0, bar + (B_FULL + s) * 8);
                }
                #pragma unroll 1
                for (int s = 0; s < 8; s++) {
                    mbar_wait(bar + (B_EMPTY + s) * 8, 1);
                    mbar_expect_tx(bar + (B_FULL + s) * 8, STB);
                    tma3d(sb + s * STB, &P.q, 64 * j, 64 * s, 0, bar + (B_FULL + s) * 8);
                    tma3d(sb + s * STB + 8192, &P.w1b, 176 * j + 128, 64 * s, 0, bar + (B_FULL + s) * 8);
                }
                #pragma unroll 1
                for (int p = 0; p < 2; p++) {
                    const int ch = 4 * r + 2 * (cc ^ p ^ 1);
                    #pragma unroll
                    for (int s = 0; s < 8; s++) {
                        const int jj = j ^ ((s >> 1) & 1);
                        if (s < 6 || p == 0) {
                            mbar_wait(bar + (B_EMPTY + s) * 8, p);
                            mbar_expect_tx(bar + (B_FULL + s) * 8, STB);
                            if (s == 5 || s == 7) tma3d(sb + s * STB, &P.wo, 0, 64 * jj, ch, bar + (B_FULL + s) * 8);
                            else tma3d(sb + s * STB, &P.w2, 0, 176 * jj + (s < 4 ? 64 * (s & 1) : 128), ch, bar + (B_FULL + s) * 8);
                        }
                    }
                    if (p == 0) {
                        mbar_wait_cluster(bar + B_RXFREE2 * 8, 0); mbar_wait_cluster(bar + (B_RXFREE2 + 1) * 8, 0);
                        mbar_expect_tx(bar + B_XRES * 8, STB);
                        tma3d(sb + OFF_XRES, &P.xr, 0, m * 128, 4 * r + c, bar + B_XRES * 8);
                        mbar_wait(bar + B_PBDONE * 8, 0);
                        mbar_expect_tx(bar + B_FULLB * 8, STB);
                        tma3d(sb + OFF_INC, &P.w2, 0, 176 * (j ^ 1) + 128, 4 * r + 2 * cc, bar + B_FULLB * 8);
                        mbar_expect_tx(bar + (B_FULLB + 1) * 8, STB);
                        tma3d(sb + OFF_INC + STB, &P.wo, 0, 64 * (j ^ 1), 4 * r + 2 * cc, bar + (B_FULLB + 1) * 8);
                    }
                }
            }
        } else if (warp == 11) {
            if (lane < 8) {
                const CUtensorMap* tm = &P.kv + lane;
                asm volatile("prefetch.tensormap [%0];" :: "l"(tm) : "memory");
            }
            if ((sb & 0x3FFFF) != SMEM_BASE) __trap();
            sts128(sb + OFF_ONES + lane * 16, ONES2, ONES2, ONES2, ONES2);
            sts128(sb + OFF_ONES + 512 + lane * 16, ONES2, ONES2, ONES2, ONES2);
            fence_async_smem();
            bar_sync(0, 384);
            uint32_t bv[3];
            #pragma unroll
            for (int u = 0; u < 3; u++) bv[u] = (lane + 32 * u < 88 && 88 * j + lane + 32 * u < 688) ? __ldg((const uint32_t*)P.b1 + 88 * j + lane + 32 * u) : 0u;
            const uint32_t b2v = __ldg((const uint32_t*)(P.b2 + 256 * r + 64 * c) + lane);
            asm volatile("barrier.cluster.arrive.relaxed.aligned;" ::: "memory");
            #pragma unroll
            for (int u = 0; u < 3; u++) {
                const int idx = lane + 32 * u;
                if (idx < 88) sts32(sb + OFF_B1 + (idx & 3) * 96 + (idx >> 2) * 4, mul2(bv[u], 0x3F003F00u));
            }
            sts32(sb + OFF_B2 + (lane & 3) * 32 + (lane >> 2) * 4, b2v);
            fence_async_smem();
            __syncwarp();
            if (lane == 0) {
                mbar_arrive(bar + B_MISC * 8);
                unsigned long long t0, t1;
                asm volatile("mov.u64 %0, %globaltimer;" : "=l"(t0));
                while (true) {
                    uint32_t ok;
                    asm volatile("{ .reg .pred p; mbarrier.try_wait.parity.shared::cta.b64 p, [%1], 0; selp.u32 %0, 1, 0, p; }" : "=r"(ok) : "r"(bar + B_DONE * 8) : "memory");
                    if (ok) break;
                    asm volatile("mov.u64 %0, %globaltimer;" : "=l"(t1));
                    if (t1 - t0 > 2000000000ull) __trap();
                }
            }
        } else {
            const int g = warp - 9;
            unsigned ep;
            asm volatile("ld.relaxed.gpu.global.u32 %0, [%1];" : "=r"(ep) : "l"(&g_epoch) : "memory");
            {
                uint32_t v[8];
                #pragma unroll
                for (int u = 0; u < 8; u++) v[u] = __ldg((const uint32_t*)P.wphi + j * 512 + g * 256 + u * 32 + lane);
                bar_sync(0, 384);
                asm volatile("barrier.cluster.arrive.relaxed.aligned;" ::: "memory");
                #pragma unroll
                for (int u = 0; u < 8; u++) {
                    const int row = u * 4 + (lane >> 3);
                    const uint32_t lo = g ? 0u : v[u], hi = g ? v[u] : 0u;
                    sts128(sb + OFF_WBIG + g * 4096 + row * 128 + (((lane ^ row) & 7) << 4), u < 4 ? lo : 0u, u < 4 ? 0u : lo, u < 4 ? hi : 0u, u < 4 ? 0u : hi);
                }
                fence_async_smem();
                __syncwarp();
                if (lane == 0) mbar_arrive(bar + B_MISC * 8);
            }
            const float* kvg = g_kv[ep & 1][j];
            unsigned* cnt = &g_cnt[ep & 1][j][0];
            {
                float4* z = (float4*)&g_kv[(ep + 1) & 1][j][m * 136];
                if (lane < 17) z[g * 17 + lane] = make_float4(0.f, 0.f, 0.f, 0.f);
                if (m == 0 && lane == 0) g_cnt[(ep + 1) & 1][j][0] = 0;
            }
            asm volatile("barrier.cluster.wait.acquire.aligned;" ::: "memory");
            if (lane == 0) {
                sts32(sb + OFF_EP, ep);
                mbar_wait(bar + (B_KVST + g) * 8, 0);
                TSW(1 + g, 4);
                asm volatile("cp.reduce.async.bulk.global.shared::cta.bulk_group.add.f32 [%0], [%1], 8192;"
                    :: "l"(kvg), "r"(sb + OFF_INC + g * 32768 + R_KVP) : "memory");
                asm volatile("cp.reduce.async.bulk.global.shared::cta.bulk_group.add.f32 [%0], [%1], 512;"
                    :: "l"(kvg + 2048), "r"(sb + OFF_KVB + g * 512) : "memory");
                asm volatile("cp.async.bulk.commit_group;" ::: "memory");
                asm volatile("cp.async.bulk.wait_group.read 0;" ::: "memory");
                asm volatile("mbarrier.arrive.relaxed.cluster.shared::cluster.b64 _, [%0];" :: "r"(mapa(bar + (B_RXFREE + g) * 8, r ^ 1)) : "memory");
                asm volatile("cp.async.bulk.wait_group 0;" ::: "memory");
                asm volatile("red.relaxed.gpu.global.add.u32 [%0], 1;" :: "l"(cnt) : "memory");
                if (g == 1) {
                    unsigned v;
                    do { asm volatile("ld.relaxed.gpu.global.u32 %0, [%1];" : "=r"(v) : "l"(cnt) : "memory"); } while (v < 32);
                    TSW(1 + g, 1);
                    asm volatile("fence.proxy.async.global;" ::: "memory");
                    mbar_expect_tx(bar + B_KVRAW * 8, KV_FLOATS * 4);
                    asm volatile("cp.async.bulk.shared::cluster.global.mbarrier::complete_tx::bytes [%0], [%1], %2, [%3];"
                        :: "r"(sb + OFF_KVB), "l"(kvg), "r"(KV_FLOATS * 4), "r"(bar + B_KVRAW * 8) : "memory");
                }
            }
            __syncwarp();
            mbar_wait(bar + B_KVRAW * 8, 0);
            TSW(1 + g, 3);
            #pragma unroll 1
            for (int h = 2 * g; h < 2 * g + 2; h++) {
                const uint32_t kb = sb + OFF_KVB + h * 2048;
                uint32_t w[8];
                #pragma unroll
                for (int u = 0; u < 4; u++) {
                    uint32_t v[4];
                    lds128(v, kb + u * 512 + lane * 16);
                    w[2 * u] = pack2(__uint_as_float(v[0]), __uint_as_float(v[1])); w[2 * u + 1] = pack2(__uint_as_float(v[2]), __uint_as_float(v[3]));
                }
                const float z = __uint_as_float(lds32(sb + OFF_KVB + 8192 + h * 128 + lane * 4));
                const uint32_t zw = pack2(z, z);
                __syncwarp();
                #pragma unroll
                for (int u = 0; u < 8; u++) sts32(kb + (u >> 2) * 768 + (u & 3) * 128 + lane * 4, w[u]);
                sts128(kb + (lane >> 4) * 768 + 512 + (lane & 15) * 16, zw, zw, zw, zw);
            }
            fence_async_smem();
            __syncwarp();
            if (lane == 0) mbar_arrive(bar + B_KVRDY * 8);
            TSW(1 + g, 2);
            const uint32_t* fp = (const uint32_t*)&g_flag[m * 8 + j][g * 3] + (lane & 7);
            mbar_wait(bar + B_PBDONE * 8, 0);
            #pragma unroll
            for (int late = 0; late < 2; late++) {
                uint32_t f;
                do {
                    asm volatile("ld.relaxed.gpu.global.u32 %0, [%1];" : "=r"(f) : "l"(late ? fp - (lane & 4) : fp + 4) : "memory");
                } while (__any_sync(0xffffffffu, f != ep + 1));
                if (lane == 0) TP(32 + 2 * late + g);
                mbar_wait(bar + (B_EMPTY + ((late | g) ? 7 : 1)) * 8, 1);
                if (elect_one()) {
                    const uint32_t bytes = late ? 8192 : 16384, tbar = bar + (B_TILE + 2 * late + g) * 8;
                    mbar_expect_tx(tbar, bytes);
                    asm volatile("cp.async.bulk.shared::cluster.global.mbarrier::complete_tx::bytes [%0], [%1], %2, [%3];"
                        :: "r"(late ? sb + 6 * STB + g * 65536 : sb + (g ? OFF_INC + 40960 : OFF_WBIG)), "l"(g_part + (size_t)((m * 8 + j) * 6 + g * 3 + 1 - late) * 512), "r"(bytes), "r"(tbar) : "memory");
                }
                __syncwarp();
            }
        }
    } else {
        asm volatile("setmaxnreg.inc.sync.aligned.u32 240;");
        bar_sync(0, 384);
        asm volatile("barrier.cluster.arrive.relaxed.aligned;" ::: "memory");
        const int wg = __shfl_sync(0xffffffffu, warp >> 2, 0), w = warp & 3, t = lane & 3, g = lane >> 2, tw = tid & 127;
        const uint32_t reg = sb + OFF_INC + wg * 32768;
        const int lrow = 16 * w + (lane & 15);
        const uint32_t swz = ((lane >> 4) ^ (lane & 7)) << 4;
        const uint32_t phia = reg + (t >> 1) * 8192 + (16 * w + g) * 128 + (((4 * (t & 1)) ^ (t & 2) ^ g) << 4);
        constexpr uint64_t dB = (uint64_t)(SMEM_BASE >> 4) | desc_hi(8192, 1024, 1);

        uint32_t A[32][4];
        {
            const uint32_t xst = sb + (wg ? OFF_INC : 4 * STB) + lrow * 128;
            #define LOADX(i) do { mbar_wait(bar + (B_XFULL + 4 * wg + (i)) * 8, 0); if ((i) == 0 || (i) == 3) TS((i) ? 25 : 24); \
                _Pragma("unroll") for (int k = 8 * (i); k < 8 * (i) + 8; k++) ldsm4(A[k], xst + (k >> 2) * 8192 + (swz ^ (32 * (k & 3)))); } while (0)
            float st[4];
            if (wg == 0) {
                float s4[2][4], q4[4];
                #pragma unroll
                for (int i = 0; i < 4; i++) { s4[0][i] = 0.f; s4[1][i] = 0.f; q4[i] = 0.f; }
                LOADX(0);
                #pragma unroll
                for (int i = 0; i < 4; i++) {
                    if (i < 3) LOADX(i + 1);
                    uint32_t c[4];
                    #pragma unroll
                    for (int k = 8 * i; k < 8 * i + 8; k++) {
                        mma_ones(s4[k & 1], A[k]);
                        #pragma unroll
                        for (int e = 0; e < 4; e++) c[e] = (k & 7) ? fma2(A[k][e], A[k][e], c[e]) : mul2(A[k][e], A[k][e]);
                    }
                    mma_ones(q4, c);
                }
                st[0] = s4[0][0] + s4[1][0]; st[1] = s4[0][2] + s4[1][2]; st[2] = q4[0]; st[3] = q4[2];
            } else {
                #pragma unroll
                for (int i = 0; i < 4; i++) st[i] = 0.f;
                LOADX(0);
                #pragma unroll
                for (int i = 0; i < 4; i++) {
                    if (i < 3) LOADX(i + 1);
                    sum8(A + 8 * i, st[0], st[1]);
                    sumsq8(A + 8 * i, st[2], st[3]);
                }
                #pragma unroll
                for (int o = 1; o <= 2; o <<= 1) {
                    #pragma unroll
                    for (int i = 0; i < 4; i++) st[i] += __shfl_xor_sync(0xffffffffu, st[i], o);
                }
            }
            const float mean0 = st[0] * (1.f / 512.f), mean1 = st[1] * (1.f / 512.f), q0 = st[2] * (1.f / 512.f), q1 = st[3] * (1.f / 512.f);
            const float var0 = fmaf(-mean0, mean0, q0), var1 = fmaf(-mean1, mean1, q1);
            const float rs0 = rsq(var0 + 1e-5f), rs1 = rsq(var1 + 1e-5f);
            uint32_t sc0 = pack2(rs0, rs0), sc1 = pack2(rs1, rs1);
            uint32_t of0 = pack2(-mean0 * bflo(sc0), -mean0 * bflo(sc0)), of1 = pack2(-mean1 * bflo(sc1), -mean1 * bflo(sc1));
            if (lane == 0 && of0 != 0xFFFFFFFFu) mbar_arrive(bar + (B_XFREE + wg) * 8);
            if (__any_sync(0xffffffffu, !(var0 >= 0.5f * q0) || !(var1 >= 0.5f * q1))) {
                uint32_t mb0 = pack2(-mean0, -mean0), mb1 = pack2(-mean1, -mean1);
                #pragma unroll
                for (int i = 0; i < 4; i++) st[i] = 0.f;
                #pragma unroll
                for (int k = 0; k < 32; k += 8) { norm4(A + k, ONES2, ONES2, mb0, mb1); norm4(A + k + 4, ONES2, ONES2, mb0, mb1); sum8(A + k, st[0], st[1]); sumsq8(A + k, st[2], st[3]); }
                #pragma unroll
                for (int o = 1; o <= 2; o <<= 1) {
                    #pragma unroll
                    for (int i = 0; i < 4; i++) st[i] += __shfl_xor_sync(0xffffffffu, st[i], o);
                }
                const float e0 = st[0] * (1.f / 512.f), e1 = st[1] * (1.f / 512.f);
                const float r0 = rsq(fmaxf(fmaf(-e0, e0, st[2] * (1.f / 512.f)), 0.f) + 1e-5f), r1 = rsq(fmaxf(fmaf(-e1, e1, st[3] * (1.f / 512.f)), 0.f) + 1e-5f);
                sc0 = pack2(r0, r0); sc1 = pack2(r1, r1);
                const float d0 = -bflo(mb0) - bflo(pack2(e0 - bflo(mb0), 0.f)), d1 = -bflo(mb1) - bflo(pack2(e1 - bflo(mb1), 0.f));
                of0 = pack2(d0 * bflo(sc0), d0 * bflo(sc0)); of1 = pack2(d1 * bflo(sc1), d1 * bflo(sc1));
            }
            TS(0);
            norm4(A, sc0, sc1, of0, of1);
            if (wg == 1) {
                #pragma unroll
                for (int s = 1; s < 8; s++) norm4(A + 4 * s, sc0, sc1, of0, of1);
                TS(29);
                bar_sync(6, 256);
            }
            float acc[64];
            #pragma unroll
            for (int s = 0; s < 8; s++) {
                wait_full(sb, s, 0);
                MMA_STAGE(SPLIT0, if (s == 0 && k == 0) wgmma_rs128_first(acc, A[0], d); else wgmma_rs128(acc, A[4 * s + k], d));
                if (s == 0) TS(1);
                TSS(0, s);
                if (s == PP_STAGE) bar_arrive(6 - wg, 256);
                if (wg == 0 && s < 7) norm4(A + 4 * s + 4, sc0, sc1, of0, of1);
                if (s > 0 || SPLIT0) STAGE_WAIT();
                if (s > 0) release(sb, s - 1, lane);
            }
            mbar_wait(bar + B_MISC * 8, 0);
            wg_wait<0>();
            release(sb, 7, lane);
            TS(2);

            float p[32];
            uint32_t ka[4][4];
            logits_issue(acc, ka, p);
            mbar_wait(bar + (B_XFREE + 1) * 8, 0);
            {
                const uint32_t va = reg + R_V + lrow * 64 + (((lane >> 4) ^ ((lane >> 1) & 3)) << 4);
                #pragma unroll
                for (int h = 0; h < 4; h++) {
                    const float* v = acc + 32 + 8 * h;
                    stsm4((va ^ (32 * (h & 1))) + (h >> 1) * 4096, pack2(v[0], v[1]), pack2(v[2], v[3]), pack2(v[4], v[5]), pack2(v[6], v[7]));
                }
            }
            wg_wait<0>();
            TS(19);
            features(p, phia);
            TS(3);
            fence_async_smem();
            bar_sync(1 + wg, 128);
            float kv0[20], kv1[20];
            wg_fence();
            kv_mma(kv0, kv1, wg);
            const uint32_t kvo = reg + R_KVP + lane * 16, zo = sb + OFF_KVB + wg * 512 + (w * 16 + g) * 4;
            wg_wait<1>();
            store_kv(kv0, kvo + w * 1024, zo, w >> 1, t);
            wg_wait<0>();
            TS(16);
            store_kv(kv1, kvo + 4096 + (w ^ 1) * 1024, (zo ^ 64) + 256, w >> 1, t);
        }
        TS(4);
        const uint32_t rreg = mapa(reg + tw * 16, r ^ 1);
        const uint32_t park = sb + OFF_XRES + wg * 8192 + tw * 16;
        uint32_t Ha[8][4];
        {
            float acc[64];
            bar_sync(5 + wg, 256);
            #pragma unroll
            for (int s = 0; s < 8; s++) {
                wait_full(sb, s, 1);
                MMA_STAGE(SPLIT0, if (s == 0 && k == 0) wgmma_rs128_first(acc, A[0], d); else wgmma_rs128(acc, A[4 * s + k], d));
                if (s == 0) TS(20);
                TSS(1, s);
                if (s == PP_STAGE) bar_arrive(6 - wg, 256);
                if (s == 1) {
                    fence_async_smem();
                    __syncwarp();
                    if (lane == 0) mbar_arrive(bar + (B_KVST + wg) * 8);
                }
                if (s > 0 || SPLIT0) STAGE_WAIT();
                if (s > 0) release(sb, s - 1, lane);
            }
            uint32_t bw[4][4];
            #pragma unroll
            for (int i = 0; i < 4; i++) lds128(bw[i], sb + OFF_B1 + t * 96 + i * 16);
            wg_wait<0>();
            release(sb, 7, lane);
            TS(5);
            #pragma unroll
            for (int i = 7; i >= 0; i--) {
                pre_gelu(Ha[i], acc + 8 * i, bw[i >> 1][2 * (i & 1)], bw[i >> 1][2 * (i & 1) + 1]);
                gelu4(Ha[i]);
                sts128(i >= 4 ? park + (i - 4) * 2048 : reg + tw * 16 + (8 + i) * 2048, Ha[i][0], Ha[i][1], Ha[i][2], Ha[i][3]);
            }
            fence_async_smem();
            mbar_wait_cluster(bar + (B_RXFREE + wg) * 8, 0);
            bar_sync(1 + wg, 128);
            const uint32_t rbar = mapa(bar + (B_RXA + wg) * 8, r ^ 1);
            if (tw == 0) {
                asm volatile("cp.async.bulk.shared::cluster.shared::cta.mbarrier::complete_tx::bytes [%0], [%1], 8192, [%2];"
                    :: "r"(rreg), "r"(reg + 16384), "r"(rbar) : "memory");
                asm volatile("cp.async.bulk.shared::cluster.shared::cta.mbarrier::complete_tx::bytes [%0], [%1], 8192, [%2];"
                    :: "r"(rreg + 8192), "r"(park), "r"(rbar) : "memory");
            }
        }
        TS(6);
        uint32_t Hb[7][4];
        uint32_t Pa[8][4], Pb[7][4];
        {
            float acc[56];
            bar_sync(5 + wg, 256);
            #pragma unroll
            for (int s = 0; s < 8; s++) {
                wait_full(sb, s, 0);
                MMA_STAGE(SPLIT0, if (s == 0 && k == 0) wgmma_rs112_first(acc, A[0], d); else wgmma_rs112(acc, A[4 * s + k], d));
                if (s == 0) TS(21);
                TSS(2, s);
                if (s == PP_STAGE) bar_arrive(6 - wg, 256);
                if (s == 4) mbar_wait_cluster(bar + (B_RXA + wg) * 8, 0);
                #pragma unroll
                for (int i = 3 * s - 6; i < 3 * s - 3; i++) {
                    if (i >= 0 && i < 4) lds128(Ha[i], reg + tw * 16 + (8 + i) * 2048);
                    else if (i >= 4 && i < 8) lds128(Ha[i], park + (i - 4) * 2048);
                    else if (i >= 8 && i < 16) lds128(Pa[i - 8], reg + (i - 8) * 2048 + tw * 16);
                }
                if (s > 0 || SPLIT0) STAGE_WAIT();
                if (s > 0) release(sb, s - 1, lane);
            }
            uint32_t bw[2][4];
            lds128(bw[0], sb + OFF_B1 + t * 96 + 64); lds128(bw[1], sb + OFF_B1 + t * 96 + 80);
            wg_wait<0>();
            release(sb, 7, lane);
            TS(7);
            float p[32];
            uint32_t qa[4][4];
            {
                #pragma unroll
                for (int i = 0; i < 3; i++) pre_gelu(Hb[i], acc + 32 + 8 * i, bw[i >> 1][2 * (i & 1)], bw[i >> 1][2 * (i & 1) + 1]);
            }
            logits_issue(acc, qa, p);
            wg_wait<0>();
            bar_sync(1 + wg, 128);
            if (tw == 0) asm volatile("mbarrier.arrive.relaxed.cluster.shared::cluster.b64 _, [%0];" :: "r"(mapa(bar + (B_RXFREE2 + wg) * 8, r ^ 1)) : "memory");
            TS(17);
            #pragma unroll
            for (int i = 0; i < 3; i++) gelu4(Hb[i]);
            features(p, phia);
            TS(8);
            fence_async_smem();
            mbar_wait_cluster(bar + (B_RXFREE2 + wg) * 8, 0);
            {
                const uint32_t rbar = mapa(bar + (B_RXB + wg) * 8, r ^ 1);
                #pragma unroll
                for (int i = 0; i < 3; i++) st_async4(rreg + (8 + i) * 2048, Hb[i], rbar);
            }
            mbar_wait(bar + B_KVRDY * 8, 0);
            TS(9);
        }
        const unsigned ep = lds32(sb + OFF_EP);
        const uint32_t tag = (ep + 1) & 1;
        #define PART(o) (g_part + (size_t)((m * 8 + 2 * (o) + r) * 6 + wg * 3 + (c ^ (o)) - 1) * 512 + tw)
        #define FLAG(o) (&g_flag[m * 8 + 2 * (o) + r][wg * 3 + (c ^ (o)) - 1])
        float own[32];
        {
            float o[4][12], acc[64];
            bar_sync(5 + wg, 256);
            wg_fence();
            readout_mma(o, wg);
            wg_commit();
            #pragma unroll
            for (int s = 0; s < 8; s++) {
                wait_full(sb, s, 1);
                MMA_STAGE(false, if (s == 0 && k == 0) wgmma_rs128_first(acc, Ha[0], d); else if (G2_HAS(s, k)) wgmma_rs128(acc, G2_A(s, k), d));
                if (s == 0) TS(22);
                TSS(3, s);
                if (s == PP_STAGE) bar_arrive(6 - wg, 256);
                if (s == 1) {
                    wg_wait<2>();
                    const uint32_t rbar = mapa(bar + (B_RXC + wg) * 8, r ^ 1);
                    #pragma unroll
                    for (int h = 0; h < 4; h++) {
                        const float r0 = rcp(o[h][8] + 1e-6f), r1 = rcp(o[h][10] + 1e-6f);
                        Hb[3 + h][0] = pack2(o[h][0] * r0, o[h][1] * r0); Hb[3 + h][1] = pack2(o[h][2] * r1, o[h][3] * r1);
                        Hb[3 + h][2] = pack2(o[h][4] * r0, o[h][5] * r0); Hb[3 + h][3] = pack2(o[h][6] * r1, o[h][7] * r1);
                        st_async4(rreg + (11 + h) * 2048, Hb[3 + h], rbar);
                    }
                    TS(10);
                }
                if (s == 3) {
                    mbar_wait_cluster(bar + (B_RXB + wg) * 8, 0);
                    #pragma unroll
                    for (int i = 0; i < 3; i++) lds128(Pb[i], reg + (8 + i) * 2048 + tw * 16);
                }
                if (s == 5) {
                    mbar_wait_cluster(bar + (B_RXC + wg) * 8, 0);
                    #pragma unroll
                    for (int i = 3; i < 7; i++) lds128(Pb[i], reg + (8 + i) * 2048 + tw * 16);
                }
                if (s == 7 && wg == 0 && lane == 0) mbar_arrive(bar + B_PBDONE * 8);
                if (s > 0) { STAGE_WAIT(); release(sb, s - 1, lane); }
            }
            wg_wait<0>();
            release(sb, 7, lane);
            TS(11);
            uint32_t pk[8][4];
            pack_tile(pk, acc, tag);
            mbar_wait(bar + B_XRES * 8, pk[7][3] == 0xFFFFFFFFu);
            uint32_t bw[2][4];
            lds128(bw[0], sb + OFF_B2 + t * 32); lds128(bw[1], sb + OFF_B2 + t * 32 + 16);
            #pragma unroll
            for (int i = 0; i < 4; i++) {
                uint32_t xv[4];
                ldsm4(xv, sb + OFF_XRES + wg * 8192 + lrow * 128 + (swz ^ (32 * i)));
                #pragma unroll
                for (int e = 0; e < 4; e++) {
                    const uint32_t b = bw[i >> 1][2 * (i & 1) + (e >> 1)];
                    own[8 * i + 2 * e] = bflo(xv[e]) + bflo(b); own[8 * i + 2 * e + 1] = bfhi(xv[e]) + bfhi(b);
                }
            }
            TS(26);
            #pragma unroll
            for (int i = 0; i < 4; i++) {
                mbar_wait(bar + (B_EMPTY + i) * 8, i ? 1 : 1 ^ never(own[0], own[31]));
                const int oc = 2 * (cc ^ 1) + (i >> 1);
                stg128(PART(oc) + (2 * (i & 1)) * 128, pk[2 * i]); stg128(PART(oc) + (2 * (i & 1) + 1) * 128, pk[2 * i + 1]);
                if (i & 1) set_flag(FLAG(oc), w, ep + 1, lane);
            }
            TS(12);
        }
        const uint32_t tb = sb + 6 * STB + wg * 65536;
        const uint4* const mine = g_part + (size_t)((m * 8 + j) * 6 + wg * 3) * 512 + tw;
        uint32_t u[8][4];
        #pragma unroll
        for (int hf = 0; hf < 2; hf++) {
            float oth[32];
            const uint32_t dlo = (uint32_t)dB + ((c & 1) ^ hf ^ 1) * 512;
            bar_sync(5 + wg, 256);
            #pragma unroll
            for (int s = 0; s < 8; s++) {
                if (hf == 0) { if (s < 6) wait_full(sb, s, 0); else mbar_wait(bar + (B_FULLB + s - 6) * 8, 0); }
                if (hf == 0 || s == 0 || s == TA_AT + 1) wg_fence();
                #pragma unroll
                for (int k = 0; k < 4; k++) {
                    const uint32_t d = dlo + (((s < 6 ? s : s + 2) * STB + k * 2048) >> 4);
                    if (hf == 0) { if (s == 0 && k == 0) wgmma_rs64r_first(oth, Ha[0], d); else if (G2_HAS(s, k)) wgmma_rs64r(oth, G2_A(s, k), d); }
                    else if (G2_HAS(s, k)) wgmma_rs64r(own, G2_A(s, k), d);
                }
                if (s == 0) TS(hf ? 27 : 23);
                TSS(4 + hf, s);
                if (s == PPB_STAGE && (hf & wg) == 0) bar_arrive(6 - wg, 256);
                if (hf == 1 && s == TA_AT) {
                    mbar_wait(bar + (B_TILE + wg) * 8, 0);
                    #pragma unroll
                    for (int i = 0; i < 8; i++) lds128(u[i], sb + (wg ? OFF_INC + 40960 : OFF_WBIG) + tw * 16 + i * 2048);
                }
            }
            wg_commit();
            if (hf == 0) {
                wg_wait<0>();
                TS(13);
                uint32_t pk[4][4];
                pack_tile(pk, oth, tag);
                #pragma unroll
                for (int i = 0; i < 4; i++) stg128(PART(c ^ 1) + i * 128, pk[i]);
                set_flag(FLAG(c ^ 1), w, ep + 1, lane);
                TS(30);
            }
        }
        {
            check_tile(u, mine + 512, tag);
            uint32_t v[4][4];
            #pragma unroll
            for (int i = 0; i < 16; i++) u[i >> 2][i & 3] = add2(u[i >> 2][i & 3], u[4 + (i >> 2)][i & 3]);
            TS(18);
            mbar_wait(bar + (B_TILE + 2 + wg) * 8, u[3][3] == 0xFFFFFFFFu);
            #pragma unroll
            for (int i = 0; i < 4; i++) lds128(v[i], tb + tw * 16 + i * 2048);
            check_tile(v, mine, tag);
            if (lane == 0) mbar_arrive(bar + B_DONE * 8);
            TS(14);
            wg_wait<0>();
            const uint32_t ost = tb + 24576 + w * 2048;
            #pragma unroll
            for (int i = 0; i < 4; i++) {
                uint32_t o[4];
                #pragma unroll
                for (int e = 0; e < 4; e++) {
                    const uint32_t y = add2(u[i][e], v[i][e]);
                    o[e] = pack2(own[8 * i + 2 * e] + bflo(y), own[8 * i + 2 * e + 1] + bfhi(y));
                }
                stsm4(ost + (lane & 15) * 128 + (swz ^ (32 * i)), o[0], o[1], o[2], o[3]);
            }
            TS(28);
            fence_async_smem();
            __syncwarp();
            if (elect_one()) {
                asm volatile("cp.async.bulk.tensor.3d.global.shared::cta.bulk_group [%0, {%2, %3, %4}], [%1];"
                    :: "l"(&P.out), "r"(ost), "r"(0), "r"(m * 128 + wg * 64 + 16 * w), "r"(4 * r + c) : "memory");
                asm volatile("cp.async.bulk.commit_group;" ::: "memory");
                if (blockIdx.x == 0 && warp == 4) asm volatile("st.relaxed.gpu.global.u32 [%0], %1;" :: "l"(&g_epoch), "r"(ep + 1) : "memory");
                asm volatile("cp.async.bulk.wait_group.read 0;" ::: "memory");
            }
        }
        TS(15);
        TSDUMP();
    }
}

typedef CUresult (*EncFn)(CUtensorMap*, CUtensorMapDataType, cuuint32_t, void*, const cuuint64_t*, const cuuint64_t*, const cuuint32_t*,
                          const cuuint32_t*, CUtensorMapInterleave, CUtensorMapSwizzle, CUtensorMapL2promotion, CUtensorMapFloatOOBfill);

void encode(EncFn enc, CUtensorMap* tm, const void* base, int rank, cuuint64_t d0, cuuint64_t d1, cuuint64_t d2, cuuint64_t s1, cuuint64_t s2,
            cuuint32_t b0, cuuint32_t b1, cuuint32_t b2) {
    cuuint64_t gd[3] = {d0, d1, d2}, gs[2] = {s1, s2};
    cuuint32_t bd[3] = {b0, b1, b2}, es[3] = {1, 1, 1};
    enc(tm, CU_TENSOR_MAP_DATA_TYPE_BFLOAT16, rank, const_cast<void*>(base), gd, gs, bd, es, CU_TENSOR_MAP_INTERLEAVE_NONE,
        CU_TENSOR_MAP_SWIZZLE_128B, PROMO, CU_TENSOR_MAP_FLOAT_OOB_FILL_NONE);
}

}

extern "C" void kernel_launch(void* const* d_in, const int* in_sizes, int n_in, void* d_out, int out_size) {
    (void)in_sizes; (void)n_in; (void)out_size;
    static EncFn enc = nullptr;
    if (!enc) {
        void* fn = nullptr;
        cudaDriverEntryPointQueryResult qr;
        cudaGetDriverEntryPoint("cuTensorMapEncodeTiled", &fn, cudaEnableDefault, &qr);
        enc = (EncFn)fn;
        cudaFuncSetAttribute(fused_kernel, cudaFuncAttributeMaxDynamicSharedMemorySize, LAUNCH_SMEM);
    }
    Params P;
    encode(enc, &P.x, d_in[0], 3, 64, 2048, 8, 1024, 128, 64, 64, 2);
    encode(enc, &P.kv, d_in[1], 3, 512, 512, 3, 3072, 1024, 64, 64, 2);
    encode(enc, &P.q, d_in[1], 3, 512, 512, 3, 3072, 1024, 64, 64, 1);
    encode(enc, &P.w1a, d_in[5], 3, 1376, 512, 2, 2752, 128, 64, 64, 2);
    encode(enc, &P.w1b, d_in[5], 3, 1376, 512, 2, 2752, 128, 64, 64, 1);
    encode(enc, &P.w2, d_in[7], 3, 64, 1376, 8, 1024, 128, 64, 64, 2);
    encode(enc, &P.wo, d_in[3], 3, 64, 512, 8, 1024, 128, 64, 64, 2);
    encode(enc, &P.out, d_out, 3, 64, 2048, 8, 1024, 128, 64, 16, 1);
    encode(enc, &P.xr, d_in[0], 3, 64, 2048, 8, 1024, 128, 64, 128, 1);
    for (int k = 0; k < 64; k++) {
        int G, half, i;
        if (k < 4) { G = 0; half = 1; i = k; }
        else if (k < 36) { G = (k - 4) % 8; half = 0; i = (k - 4) / 8; }
        else { G = (k - 36) % 7 + 1; half = 1; i = (k - 36) / 7; }
        int m, c;
        if (MAPPING == 0) { m = k >> 2; c = k & 3; }
        else if (MAPPING == 1) { m = 2 * G + half; c = i; }
        else if (MAPPING == 2) { c = 2 * (G & 1) + (i & 1); m = 4 * (G >> 1) + 2 * half + (i >> 1); }
        else { c = G & 3; m = 8 * (G >> 2) + 4 * half + i; }
        P.role[k] = (uint8_t)(4 * m + c);
    }
    P.wphi = (const __nv_bfloat16*)d_in[2];
    P.b1 = (const __nv_bfloat16*)d_in[6];
    P.b2 = (const __nv_bfloat16*)d_in[8];
    fused_kernel<<<128, 384, LAUNCH_SMEM, cudaStreamPerThread>>>(P);
}
```

```cpp
#include <cuda_runtime.h>
#include <cuda_bf16.h>
#include <cuda.h>
#include <stdint.h>

#define X1_AT 1
#define PROMO CU_TENSOR_MAP_L2_PROMOTION_L2_128B
#define PPB_STAGE 7
#define SPLIT0 1
#define PREFETCH 1
#define PROF_P0 3
#define PROF_P1 4
#define OUT_TMA 0
#define STORE_GATE 2
#define PA_AT 6
#define KV_EARLY 1
#define WARM 0
#define LPIPE 1
#define CHAIN 1
#define SUMH 0
#define NORM_UP 0
#define SPLIT1 1
#define X1_MC 0
#define FINP 2
#define HB_LATE 1
#define WPF 0
#define X1PF 0
#define VPIN 0
#define WAITV 0
#define WAITHINT ""
#define QUIET 0
#define WDHINT ""
#define PP_STAGE 7

namespace {

constexpr uint32_t SMEM_BASE = 1024;
constexpr int NST = 8;
constexpr int STB = 16384;
constexpr int OFF_INC = NST * STB;
constexpr int OFF_XRES = OFF_INC + 65536;
constexpr int OFF_WBIG = OFF_XRES + 16384;
constexpr int OFF_ONES = OFF_WBIG + 8192;
constexpr int OFF_KVB = OFF_ONES + 1024;
constexpr int OFF_B1 = OFF_KVB + 8704;
constexpr int OFF_B2 = OFF_B1 + 384;
constexpr int OFF_EP = OFF_B2 + 128;
constexpr int OFF_BAR = OFF_EP + 16;
enum { B_XFULL = 0, B_FULL = 8, B_RXA = 16, B_RXB = 18, B_RXC = 20, B_RXFREE = 22, B_MISC = 24, B_XRES = 25, B_KVRAW = 26, B_RXFREE2 = 27, B_FULLB = 29, B_TILE = 33,
       B_EMPTY = 37, B_DONE = 45, B_XFREE = 46, B_KVST = 48, B_PBDONE = 50, B_HAST = 51, B_KVRDY = 53, B_NUM = 54 };
constexpr int SMEM_BYTES = OFF_BAR + B_NUM * 8;
static_assert(SMEM_BYTES <= 232448, "smem");
constexpr int R_KVP = 24576;
constexpr int R_V = 16384;
constexpr int KV_FLOATS = 2176;

__device__ __align__(128) float g_kv[2][8][KV_FLOATS];
__device__ unsigned g_cnt[2][8][32];
__device__ unsigned g_epoch;
__device__ __align__(128) uint4 g_flag[128][8];
__device__ uint4 g_part[128 * 8 * 512];
#define TS(i)
#define TP(i)
#define TSS(p, s)
#define TSW(w, i)
#define TSDUMP()
#define TG(i)
#define LAUNCH_SMEM SMEM_BYTES

struct Params {
    CUtensorMap x, kv, q, w1a, w1b, w2, wo, out, xr, w2h, woh;
    const __nv_bfloat16* wphi;
    const __nv_bfloat16* b1;
    const __nv_bfloat16* b2;
    void* outp;
    const __nv_bfloat16* xp;
    const __nv_bfloat16* wp;
};

__device__ __forceinline__ void mbar_init(uint32_t bar, uint32_t cnt) { asm volatile("mbarrier.init.shared::cta.b64 [%0], %1;" :: "r"(bar), "r"(cnt) : "memory"); }
__device__ __forceinline__ void mbar_expect_tx(uint32_t bar, uint32_t bytes) { asm volatile("mbarrier.arrive.expect_tx.shared::cta.b64 _, [%0], %1;" :: "r"(bar), "r"(bytes) : "memory"); }
__device__ __forceinline__ void mbar_arrive(uint32_t bar) { asm volatile("mbarrier.arrive.shared::cta.b64 _, [%0];" :: "r"(bar) : "memory"); }
__device__ __forceinline__ void mbar_wait(uint32_t bar, uint32_t parity) {
    asm volatile("{\n"
        ".reg .pred p;\n"
        "WL%=:\n"
        "mbarrier.try_wait.parity.shared::cta.b64 p, [%0], %1" WAITHINT ";\n"
        "@!p bra WL%=;\n"
        "}" :: "r"(bar), "r"(parity) : "memory");
}
__device__ __forceinline__ void tma3d(uint32_t dst, const CUtensorMap* tm, int c0, int c1, int c2, uint32_t bar) {
    asm volatile("cp.async.bulk.tensor.3d.shared::cluster.global.mbarrier::complete_tx::bytes [%0], [%1, {%3, %4, %5}], [%2];"
        :: "r"(dst), "l"(tm), "r"(bar), "r"(c0), "r"(c1), "r"(c2) : "memory");
}
__device__ __forceinline__ void pf3d(const CUtensorMap* tm, int c0, int c1, int c2) {
    asm volatile("cp.async.bulk.prefetch.tensor.3d.L2.global [%0, {%1, %2, %3}];" :: "l"(tm), "r"(c0), "r"(c1), "r"(c2) : "memory");
}
__device__ __forceinline__ bool elect_one() {
    uint32_t p;
    asm volatile("{ .reg .pred P; elect.sync _|P, 0xffffffff; selp.u32 %0, 1, 0, P; }" : "=r"(p));
    return p;
}
__device__ __forceinline__ void wg_fence() { asm volatile("wgmma.fence.sync.aligned;" ::: "memory"); }
__device__ __forceinline__ void wg_commit() { asm volatile("wgmma.commit_group.sync.aligned;" ::: "memory"); }
template <int N> __device__ __forceinline__ void wg_wait() { asm volatile("wgmma.wait_group.sync.aligned %0;" :: "n"(N) : "memory"); }
__device__ __forceinline__ void fence_async_smem() { asm volatile("fence.proxy.async.shared::cta;" ::: "memory"); }
__device__ __forceinline__ void bar_sync(int id, int n) { asm volatile("bar.sync %0, %1;" :: "r"(id), "r"(n) : "memory"); }
__device__ __forceinline__ void bar_arrive(int id, int n) { asm volatile("bar.arrive %0, %1;" :: "r"(id), "r"(n) : "memory"); }
__device__ __forceinline__ void ldsm4(uint32_t (&r)[4], uint32_t addr) {
    asm volatile("ldmatrix.sync.aligned.m8n8.x4.shared.b16 {%0,%1,%2,%3}, [%4];" : "=r"(r[0]), "=r"(r[1]), "=r"(r[2]), "=r"(r[3]) : "r"(addr) : "memory");
}
__device__ __forceinline__ void stsm4(uint32_t addr, uint32_t a, uint32_t b, uint32_t c, uint32_t d) {
    asm volatile("stmatrix.sync.aligned.m8n8.x4.shared.b16 [%0], {%1,%2,%3,%4};" :: "r"(addr), "r"(a), "r"(b), "r"(c), "r"(d) : "memory");
}
__device__ __forceinline__ void lds128(uint32_t (&r)[4], uint32_t addr) {
    asm volatile("ld.shared.v4.b32 {%0,%1,%2,%3}, [%4];" : "=r"(r[0]), "=r"(r[1]), "=r"(r[2]), "=r"(r[3]) : "r"(addr) : "memory");
}
__device__ __forceinline__ uint32_t lds32(uint32_t addr) { uint32_t r; asm volatile("ld.shared.b32 %0, [%1];" : "=r"(r) : "r"(addr) : "memory"); return r; }
__device__ __forceinline__ void sts128(uint32_t addr, uint32_t a, uint32_t b, uint32_t c, uint32_t d) {
    asm volatile("st.shared.v4.b32 [%0], {%1,%2,%3,%4};" :: "r"(addr), "r"(a), "r"(b), "r"(c), "r"(d) : "memory");
}
__device__ __forceinline__ void sts32(uint32_t addr, uint32_t a) { asm volatile("st.shared.b32 [%0], %1;" :: "r"(addr), "r"(a) : "memory"); }
__device__ __forceinline__ void st_async4(uint32_t addr, const uint32_t (&v)[4], uint32_t bar) {
    asm volatile("st.async.weak.shared::cluster.mbarrier::complete_tx::bytes.v4.b32 [%0], {%1,%2,%3,%4}, [%5];"
        :: "r"(addr), "r"(v[0]), "r"(v[1]), "r"(v[2]), "r"(v[3]), "r"(bar) : "memory");
}
__device__ __forceinline__ uint32_t mapa(uint32_t addr, uint32_t cta) { uint32_t r; asm("mapa.shared::cluster.u32 %0, %1, %2;" : "=r"(r) : "r"(addr), "r"(cta)); return r; }
__device__ __forceinline__ void mma_ones(float (&d)[4], const uint32_t (&a)[4]) {
    asm("mma.sync.aligned.m16n8k16.row.col.f32.bf16.bf16.f32 {%0,%1,%2,%3}, {%4,%5,%6,%7}, {%8,%8}, {%0,%1,%2,%3};"
        : "+f"(d[0]), "+f"(d[1]), "+f"(d[2]), "+f"(d[3]) : "r"(a[0]), "r"(a[1]), "r"(a[2]), "r"(a[3]), "r"(0x3F803F80u));
}
__device__ __forceinline__ uint32_t add2(uint32_t a, uint32_t b) { uint32_t r; asm("add.rn.bf16x2 %0, %1, %2;" : "=r"(r) : "r"(a), "r"(b)); return r; }
__device__ __forceinline__ uint32_t pack2(float lo, float hi) { uint32_t r; asm("cvt.rn.bf16x2.f32 %0, %1, %2;" : "=r"(r) : "f"(hi), "f"(lo)); return r; }
__device__ __forceinline__ uint32_t pack2v(float lo, float hi) { uint32_t r; asm volatile("cvt.rn.bf16x2.f32 %0, %1, %2;" : "=r"(r) : "f"(hi), "f"(lo)); return r; }
__device__ __forceinline__ float bflo(uint32_t w) { return __uint_as_float(w << 16); }
__device__ __forceinline__ float bfhi(uint32_t w) { return __uint_as_float(w & 0xffff0000u); }
__device__ __forceinline__ float ex2(float x) { float r; asm("ex2.approx.ftz.f32 %0, %1;" : "=f"(r) : "f"(x)); return r; }
__device__ __forceinline__ float rcp(float x) { float r; asm("rcp.approx.ftz.f32 %0, %1;" : "=f"(r) : "f"(x)); return r; }
__device__ __forceinline__ float rsq(float x) { float r; asm("rsqrt.approx.ftz.f32 %0, %1;" : "=f"(r) : "f"(x)); return r; }
__device__ __forceinline__ uint32_t sub2(uint32_t a, uint32_t b) { uint32_t r; asm("sub.rn.bf16x2 %0, %1, %2;" : "=r"(r) : "r"(a), "r"(b)); return r; }
__device__ __forceinline__ void wgmma_rs128_first(float (&d)[64], const uint32_t (&a)[4], uint64_t db) {
    asm volatile("{ .reg .pred p; setp.ne.b32 p, 0, 0; wgmma.mma_async.sync.aligned.m64n128k16.f32.bf16.bf16 "
        "{%0,%1,%2,%3,%4,%5,%6,%7,%8,%9,%10,%11,%12,%13,%14,%15,%16,%17,%18,%19,%20,%21,%22,%23,%24,%25,%26,%27,%28,%29,%30,%31,%32,%33,%34,%35,%36,%37,%38,%39,%40,%41,%42,%43,%44,%45,%46,%47,%48,%49,%50,%51,%52,%53,%54,%55,%56,%57,%58,%59,%60,%61,%62,%63}, {%64,%65,%66,%67}, %68, p, 1, 1, 1; }"
        : "=f"(d[0]),"=f"(d[1]),"=f"(d[2]),"=f"(d[3]),"=f"(d[4]),"=f"(d[5]),"=f"(d[6]),"=f"(d[7]),"=f"(d[8]),"=f"(d[9]),"=f"(d[10]),"=f"(d[11]),"=f"(d[12]),"=f"(d[13]),"=f"(d[14]),"=f"(d[15]),"=f"(d[16]),"=f"(d[17]),"=f"(d[18]),"=f"(d[19]),"=f"(d[20]),"=f"(d[21]),"=f"(d[22]),"=f"(d[23]),"=f"(d[24]),"=f"(d[25]),"=f"(d[26]),"=f"(d[27]),"=f"(d[28]),"=f"(d[29]),"=f"(d[30]),"=f"(d[31]),"=f"(d[32]),"=f"(d[33]),"=f"(d[34]),"=f"(d[35]),"=f"(d[36]),"=f"(d[37]),"=f"(d[38]),"=f"(d[39]),"=f"(d[40]),"=f"(d[41]),"=f"(d[42]),"=f"(d[43]),"=f"(d[44]),"=f"(d[45]),"=f"(d[46]),"=f"(d[47]),"=f"(d[48]),"=f"(d[49]),"=f"(d[50]),"=f"(d[51]),"=f"(d[52]),"=f"(d[53]),"=f"(d[54]),"=f"(d[55]),"=f"(d[56]),"=f"(d[57]),"=f"(d[58]),"=f"(d[59]),"=f"(d[60]),"=f"(d[61]),"=f"(d[62]),"=f"(d[63])
        : "r"(a[0]), "r"(a[1]), "r"(a[2]), "r"(a[3]), "l"(db));
}
__device__ __forceinline__ void wgmma_rs128(float (&d)[64], const uint32_t (&a)[4], uint64_t db) {
    asm volatile("{ .reg .pred p; setp.ne.b32 p, 1, 0; wgmma.mma_async.sync.aligned.m64n128k16.f32.bf16.bf16 "
        "{%0,%1,%2,%3,%4,%5,%6,%7,%8,%9,%10,%11,%12,%13,%14,%15,%16,%17,%18,%19,%20,%21,%22,%23,%24,%25,%26,%27,%28,%29,%30,%31,%32,%33,%34,%35,%36,%37,%38,%39,%40,%41,%42,%43,%44,%45,%46,%47,%48,%49,%50,%51,%52,%53,%54,%55,%56,%57,%58,%59,%60,%61,%62,%63}, {%64,%65,%66,%67}, %68, p, 1, 1, 1; }"
        : "+f"(d[0]),"+f"(d[1]),"+f"(d[2]),"+f"(d[3]),"+f"(d[4]),"+f"(d[5]),"+f"(d[6]),"+f"(d[7]),"+f"(d[8]),"+f"(d[9]),"+f"(d[10]),"+f"(d[11]),"+f"(d[12]),"+f"(d[13]),"+f"(d[14]),"+f"(d[15]),"+f"(d[16]),"+f"(d[17]),"+f"(d[18]),"+f"(d[19]),"+f"(d[20]),"+f"(d[21]),"+f"(d[22]),"+f"(d[23]),"+f"(d[24]),"+f"(d[25]),"+f"(d[26]),"+f"(d[27]),"+f"(d[28]),"+f"(d[29]),"+f"(d[30]),"+f"(d[31]),"+f"(d[32]),"+f"(d[33]),"+f"(d[34]),"+f"(d[35]),"+f"(d[36]),"+f"(d[37]),"+f"(d[38]),"+f"(d[39]),"+f"(d[40]),"+f"(d[41]),"+f"(d[42]),"+f"(d[43]),"+f"(d[44]),"+f"(d[45]),"+f"(d[46]),"+f"(d[47]),"+f"(d[48]),"+f"(d[49]),"+f"(d[50]),"+f"(d[51]),"+f"(d[52]),"+f"(d[53]),"+f"(d[54]),"+f"(d[55]),"+f"(d[56]),"+f"(d[57]),"+f"(d[58]),"+f"(d[59]),"+f"(d[60]),"+f"(d[61]),"+f"(d[62]),"+f"(d[63])
        : "r"(a[0]), "r"(a[1]), "r"(a[2]), "r"(a[3]), "l"(db));
}
__device__ __forceinline__ void wgmma_rs112_first(float (&d)[56], const uint32_t (&a)[4], uint64_t db) {
    asm volatile("{ .reg .pred p; setp.ne.b32 p, 0, 0; wgmma.mma_async.sync.aligned.m64n112k16.f32.bf16.bf16 "
        "{%0,%1,%2,%3,%4,%5,%6,%7,%8,%9,%10,%11,%12,%13,%14,%15,%16,%17,%18,%19,%20,%21,%22,%23,%24,%25,%26,%27,%28,%29,%30,%31,%32,%33,%34,%35,%36,%37,%38,%39,%40,%41,%42,%43,%44,%45,%46,%47,%48,%49,%50,%51,%52,%53,%54,%55}, {%56,%57,%58,%59}, %60, p, 1, 1, 1; }"
        : "=f"(d[0]),"=f"(d[1]),"=f"(d[2]),"=f"(d[3]),"=f"(d[4]),"=f"(d[5]),"=f"(d[6]),"=f"(d[7]),"=f"(d[8]),"=f"(d[9]),"=f"(d[10]),"=f"(d[11]),"=f"(d[12]),"=f"(d[13]),"=f"(d[14]),"=f"(d[15]),"=f"(d[16]),"=f"(d[17]),"=f"(d[18]),"=f"(d[19]),"=f"(d[20]),"=f"(d[21]),"=f"(d[22]),"=f"(d[23]),"=f"(d[24]),"=f"(d[25]),"=f"(d[26]),"=f"(d[27]),"=f"(d[28]),"=f"(d[29]),"=f"(d[30]),"=f"(d[31]),"=f"(d[32]),"=f"(d[33]),"=f"(d[34]),"=f"(d[35]),"=f"(d[36]),"=f"(d[37]),"=f"(d[38]),"=f"(d[39]),"=f"(d[40]),"=f"(d[41]),"=f"(d[42]),"=f"(d[43]),"=f"(d[44]),"=f"(d[45]),"=f"(d[46]),"=f"(d[47]),"=f"(d[48]),"=f"(d[49]),"=f"(d[50]),"=f"(d[51]),"=f"(d[52]),"=f"(d[53]),"=f"(d[54]),"=f"(d[55])
        : "r"(a[0]), "r"(a[1]), "r"(a[2]), "r"(a[3]), "l"(db));
}
__device__ __forceinline__ void wgmma_rs112(float (&d)[56], const uint32_t (&a)[4], uint64_t db) {
    asm volatile("{ .reg .pred p; setp.ne.b32 p, 1, 0; wgmma.mma_async.sync.aligned.m64n112k16.f32.bf16.bf16 "
        "{%0,%1,%2,%3,%4,%5,%6,%7,%8,%9,%10,%11,%12,%13,%14,%15,%16,%17,%18,%19,%20,%21,%22,%23,%24,%25,%26,%27,%28,%29,%30,%31,%32,%33,%34,%35,%36,%37,%38,%39,%40,%41,%42,%43,%44,%45,%46,%47,%48,%49,%50,%51,%52,%53,%54,%55}, {%56,%57,%58,%59}, %60, p, 1, 1, 1; }"
        : "+f"(d[0]),"+f"(d[1]),"+f"(d[2]),"+f"(d[3]),"+f"(d[4]),"+f"(d[5]),"+f"(d[6]),"+f"(d[7]),"+f"(d[8]),"+f"(d[9]),"+f"(d[10]),"+f"(d[11]),"+f"(d[12]),"+f"(d[13]),"+f"(d[14]),"+f"(d[15]),"+f"(d[16]),"+f"(d[17]),"+f"(d[18]),"+f"(d[19]),"+f"(d[20]),"+f"(d[21]),"+f"(d[22]),"+f"(d[23]),"+f"(d[24]),"+f"(d[25]),"+f"(d[26]),"+f"(d[27]),"+f"(d[28]),"+f"(d[29]),"+f"(d[30]),"+f"(d[31]),"+f"(d[32]),"+f"(d[33]),"+f"(d[34]),"+f"(d[35]),"+f"(d[36]),"+f"(d[37]),"+f"(d[38]),"+f"(d[39]),"+f"(d[40]),"+f"(d[41]),"+f"(d[42]),"+f"(d[43]),"+f"(d[44]),"+f"(d[45]),"+f"(d[46]),"+f"(d[47]),"+f"(d[48]),"+f"(d[49]),"+f"(d[50]),"+f"(d[51]),"+f"(d[52]),"+f"(d[53]),"+f"(d[54]),"+f"(d[55])
        : "r"(a[0]), "r"(a[1]), "r"(a[2]), "r"(a[3]), "l"(db));
}
__device__ __forceinline__ void wgmma_rs64_first(float (&d)[32], const uint32_t (&a)[4], uint64_t db) {
    asm volatile("{ .reg .pred p; setp.ne.b32 p, 0, 0; wgmma.mma_async.sync.aligned.m64n64k16.f32.bf16.bf16 "
        "{%0,%1,%2,%3,%4,%5,%6,%7,%8,%9,%10,%11,%12,%13,%14,%15,%16,%17,%18,%19,%20,%21,%22,%23,%24,%25,%26,%27,%28,%29,%30,%31}, {%32,%33,%34,%35}, %36, p, 1, 1, 1; }"
        : "=f"(d[0]),"=f"(d[1]),"=f"(d[2]),"=f"(d[3]),"=f"(d[4]),"=f"(d[5]),"=f"(d[6]),"=f"(d[7]),"=f"(d[8]),"=f"(d[9]),"=f"(d[10]),"=f"(d[11]),"=f"(d[12]),"=f"(d[13]),"=f"(d[14]),"=f"(d[15]),"=f"(d[16]),"=f"(d[17]),"=f"(d[18]),"=f"(d[19]),"=f"(d[20]),"=f"(d[21]),"=f"(d[22]),"=f"(d[23]),"=f"(d[24]),"=f"(d[25]),"=f"(d[26]),"=f"(d[27]),"=f"(d[28]),"=f"(d[29]),"=f"(d[30]),"=f"(d[31])
        : "r"(a[0]), "r"(a[1]), "r"(a[2]), "r"(a[3]), "l"(db));
}
__device__ __forceinline__ void wgmma_rs64(float (&d)[32], const uint32_t (&a)[4], uint64_t db) {
    asm volatile("{ .reg .pred p; setp.ne.b32 p, 1, 0; wgmma.mma_async.sync.aligned.m64n64k16.f32.bf16.bf16 "
        "{%0,%1,%2,%3,%4,%5,%6,%7,%8,%9,%10,%11,%12,%13,%14,%15,%16,%17,%18,%19,%20,%21,%22,%23,%24,%25,%26,%27,%28,%29,%30,%31}, {%32,%33,%34,%35}, %36, p, 1, 1, 1; }"
        : "+f"(d[0]),"+f"(d[1]),"+f"(d[2]),"+f"(d[3]),"+f"(d[4]),"+f"(d[5]),"+f"(d[6]),"+f"(d[7]),"+f"(d[8]),"+f"(d[9]),"+f"(d[10]),"+f"(d[11]),"+f"(d[12]),"+f"(d[13]),"+f"(d[14]),"+f"(d[15]),"+f"(d[16]),"+f"(d[17]),"+f"(d[18]),"+f"(d[19]),"+f"(d[20]),"+f"(d[21]),"+f"(d[22]),"+f"(d[23]),"+f"(d[24]),"+f"(d[25]),"+f"(d[26]),"+f"(d[27]),"+f"(d[28]),"+f"(d[29]),"+f"(d[30]),"+f"(d[31])
        : "r"(a[0]), "r"(a[1]), "r"(a[2]), "r"(a[3]), "l"(db));
}
template <uint32_t AHI, uint32_t BHI>
__device__ __forceinline__ void wgmma_ss40_first(float (&d)[20], uint32_t alo, uint32_t blo) {
    asm volatile("{ .reg .pred p; .reg .b64 da, db; setp.ne.b32 p, 0, 0; mov.b64 da, {%20, %22}; mov.b64 db, {%21, %23}; "
        "wgmma.mma_async.sync.aligned.m64n40k16.f32.bf16.bf16 "
        "{%0,%1,%2,%3,%4,%5,%6,%7,%8,%9,%10,%11,%12,%13,%14,%15,%16,%17,%18,%19}, da, db, p, 1, 1, 1, 1; }"
        : "=f"(d[0]),"=f"(d[1]),"=f"(d[2]),"=f"(d[3]),"=f"(d[4]),"=f"(d[5]),"=f"(d[6]),"=f"(d[7]),"=f"(d[8]),"=f"(d[9]),"=f"(d[10]),"=f"(d[11]),"=f"(d[12]),"=f"(d[13]),"=f"(d[14]),"=f"(d[15]),"=f"(d[16]),"=f"(d[17]),"=f"(d[18]),"=f"(d[19])
        : "r"(alo), "r"(blo), "n"(AHI), "n"(BHI));
}
template <uint32_t AHI, uint32_t BHI>
__device__ __forceinline__ void wgmma_ss40(float (&d)[20], uint32_t alo, uint32_t blo) {
    asm volatile("{ .reg .pred p; .reg .b64 da, db; setp.ne.b32 p, 1, 0; mov.b64 da, {%20, %22}; mov.b64 db, {%21, %23}; "
        "wgmma.mma_async.sync.aligned.m64n40k16.f32.bf16.bf16 "
        "{%0,%1,%2,%3,%4,%5,%6,%7,%8,%9,%10,%11,%12,%13,%14,%15,%16,%17,%18,%19}, da, db, p, 1, 1, 1, 1; }"
        : "+f"(d[0]),"+f"(d[1]),"+f"(d[2]),"+f"(d[3]),"+f"(d[4]),"+f"(d[5]),"+f"(d[6]),"+f"(d[7]),"+f"(d[8]),"+f"(d[9]),"+f"(d[10]),"+f"(d[11]),"+f"(d[12]),"+f"(d[13]),"+f"(d[14]),"+f"(d[15]),"+f"(d[16]),"+f"(d[17]),"+f"(d[18]),"+f"(d[19])
        : "r"(alo), "r"(blo), "n"(AHI), "n"(BHI));
}
template <uint32_t AHI, uint32_t BHI>
__device__ __forceinline__ void wgmma_ss24_first(float (&d)[12], uint32_t alo, uint32_t blo) {
    asm volatile("{ .reg .pred p; .reg .b64 da, db; setp.ne.b32 p, 0, 0; mov.b64 da, {%12, %14}; mov.b64 db, {%13, %15}; "
        "wgmma.mma_async.sync.aligned.m64n24k16.f32.bf16.bf16 "
        "{%0,%1,%2,%3,%4,%5,%6,%7,%8,%9,%10,%11}, da, db, p, 1, 1, 0, 1; }"
        : "=f"(d[0]),"=f"(d[1]),"=f"(d[2]),"=f"(d[3]),"=f"(d[4]),"=f"(d[5]),"=f"(d[6]),"=f"(d[7]),"=f"(d[8]),"=f"(d[9]),"=f"(d[10]),"=f"(d[11])
        : "r"(alo), "r"(blo), "n"(AHI), "n"(BHI));
}
template <uint32_t AHI, uint32_t BHI>
__device__ __forceinline__ void wgmma_ss24(float (&d)[12], uint32_t alo, uint32_t blo) {
    asm volatile("{ .reg .pred p; .reg .b64 da, db; setp.ne.b32 p, 1, 0; mov.b64 da, {%12, %14}; mov.b64 db, {%13, %15}; "
        "wgmma.mma_async.sync.aligned.m64n24k16.f32.bf16.bf16 "
        "{%0,%1,%2,%3,%4,%5,%6,%7,%8,%9,%10,%11}, da, db, p, 1, 1, 0, 1; }"
        : "+f"(d[0]),"+f"(d[1]),"+f"(d[2]),"+f"(d[3]),"+f"(d[4]),"+f"(d[5]),"+f"(d[6]),"+f"(d[7]),"+f"(d[8]),"+f"(d[9]),"+f"(d[10]),"+f"(d[11])
        : "r"(alo), "r"(blo), "n"(AHI), "n"(BHI));
}

constexpr uint32_t ONES2 = 0x3F803F80u;

__device__ __forceinline__ uint32_t fma2(uint32_t a, uint32_t b, uint32_t c) { uint32_t r; asm("fma.rn.bf16x2 %0, %1, %2, %3;" : "=r"(r) : "r"(a), "r"(b), "r"(c)); return r; }
__device__ __forceinline__ uint32_t mul2(uint32_t a, uint32_t b) { uint32_t r; asm("mul.rn.bf16x2 %0, %1, %2;" : "=r"(r) : "r"(a), "r"(b)); return r; }
__device__ __forceinline__ uint32_t never(float a, float b) { return (__float_as_uint(a) & __float_as_uint(b)) == 0xFFFFFFFFu; }
__device__ __forceinline__ void norm4(uint32_t (*A)[4], uint32_t s0, uint32_t s1, uint32_t o0, uint32_t o1) {
    #pragma unroll
    for (int k = 0; k < 4; k++) { A[k][0] = fma2(A[k][0], s0, o0); A[k][1] = fma2(A[k][1], s1, o1); A[k][2] = fma2(A[k][2], s0, o0); A[k][3] = fma2(A[k][3], s1, o1); }
}
__device__ __forceinline__ void stats8(const uint32_t (*A)[4], uint32_t (&o)[4]) {
    uint32_t c[8], q[4];
    #pragma unroll
    for (int i = 0; i < 8; i++) c[i] = add2(add2(A[i & 4][i & 3], A[(i & 4) + 1][i & 3]), add2(A[(i & 4) + 2][i & 3], A[(i & 4) + 3][i & 3]));
    #pragma unroll
    for (int k = 0; k < 8; k++) {
        #pragma unroll
        for (int i = 0; i < 4; i++) q[i] = k ? fma2(A[k][i], A[k][i], q[i]) : mul2(A[k][i], A[k][i]);
    }
    o[0] = add2(add2(c[0], c[4]), add2(c[2], c[6])); o[1] = add2(add2(c[1], c[5]), add2(c[3], c[7]));
    o[2] = add2(q[0], q[2]); o[3] = add2(q[1], q[3]);
}
__host__ __device__ constexpr uint64_t desc_hi(uint32_t lbo, uint32_t sbo, uint32_t swz) { return ((uint64_t)(lbo >> 4) << 16) | ((uint64_t)(sbo >> 4) << 32) | ((uint64_t)swz << 62); }

__device__ __forceinline__ void logits_issue(const float* acc, uint32_t (&a)[4][4], float (&p)[32]) {
    constexpr uint64_t dW = (uint64_t)((SMEM_BASE + OFF_WBIG) >> 4) | desc_hi(8192, 1024, 1);
    #pragma unroll
    for (int h = 0; h < 4; h++) {
        const float* k = acc + 8 * h;
        a[h][0] = pack2(k[0], k[1]); a[h][1] = pack2(k[2], k[3]); a[h][2] = pack2(k[4], k[5]); a[h][3] = pack2(k[6], k[7]);
    }
    wg_fence();
    #pragma unroll
    for (int h = 0; h < 4; h++) { if (h == 0) wgmma_rs64_first(p, a[0], dW); else wgmma_rs64(p, a[h], dW + h * 128); }
    wg_commit();
}
__device__ __forceinline__ void kv_mma(float (&kv0)[20], float (&kv1)[20], uint32_t wg) {
    constexpr uint32_t base = SMEM_BASE + OFF_INC, AHI = (uint32_t)(desc_hi(0, 1024, 1) >> 32), BHI = (uint32_t)(desc_hi(0, 512, 2) >> 32);
    const uint32_t oa = wg * 2048, ob = wg * (2048u - (2048u << 16));
    #pragma unroll
    for (int hp = 0; hp < 2; hp++) {
        #pragma unroll
        for (int ks = 0; ks < 4; ks++) {
            const uint32_t vb = base + R_V + hp * 4096 + ks * 1024;
            const uint32_t a = oa + (((base + hp * 8192 + ks * 2048) >> 4) | (512u << 16));
            const uint32_t b = ob + ((vb >> 4) | (((SMEM_BASE + OFF_ONES - vb) >> 4) << 16));
            if (hp == 0) { if (ks == 0) wgmma_ss40_first<AHI, BHI>(kv0, a, b); else wgmma_ss40<AHI, BHI>(kv0, a, b); }
            else { if (ks == 0) wgmma_ss40_first<AHI, BHI>(kv1, a, b); else wgmma_ss40<AHI, BHI>(kv1, a, b); }
        }
        wg_commit();
    }
}
__device__ __forceinline__ void readout_mma(float (&o)[4][12], uint32_t wg) {
    constexpr uint32_t base = SMEM_BASE + OFF_INC, AHI = (uint32_t)(desc_hi(0, 1024, 1) >> 32), BHI = (uint32_t)(desc_hi(0, 256, 0) >> 32);
    const uint32_t oa = wg * 2048;
    #pragma unroll
    for (int h = 0; h < 4; h++) {
        #pragma unroll
        for (int sg = 0; sg < 2; sg++) {
            const uint32_t a = oa + (((base + (h >> 1) * 8192 + 32 * ((2 * (h & 1) + sg) ^ (h >> 1))) >> 4) | (1u << 16));
            const uint32_t b = ((SMEM_BASE + OFF_KVB + h * 2048 + sg * 768) >> 4) | (8u << 16);
            if (sg == 0) wgmma_ss24_first<AHI, BHI>(o[h], a, b); else wgmma_ss24<AHI, BHI>(o[h], a, b);
        }
    }
}
__device__ __forceinline__ void features(float (&p)[32], uint32_t addr) {
    int keep = 3;
    while (true) {
        float rs[4];
        #pragma unroll
        for (int q = 0; q < 4; q++) {
            const int r = q >> 1, sg = q & 1;
            float e[16], s[8];
            #pragma unroll
            for (int i = 0; i < 16; i++) {
                float v = p[4 * (i >> 1) + 2 * r + (i & 1)];
                if (q >= 2 && i < CHAIN) v = fmaf(rs[q - 2], 0.f, v);
                e[i] = ex2(sg ? -v : v);
            }
            uint32_t w[8];
            #pragma unroll
            for (int i = 0; i < 8; i++) { s[i] = e[2 * i] + e[2 * i + 1]; w[i] = pack2(e[2 * i], e[2 * i + 1]); }
            if (SUMH) {
                const uint32_t a = add2(add2(w[0], w[1]), add2(w[2], w[3])), b = add2(add2(w[4], w[5]), add2(w[6], w[7]));
                const uint32_t y = add2(a, b);
                rs[q] = rcp(bflo(y) + bfhi(y));
            } else rs[q] = rcp(((s[0] + s[1]) + (s[2] + s[3])) + ((s[4] + s[5]) + (s[6] + s[7])));
            const uint32_t r2 = pack2(rs[q], rs[q]);
            #pragma unroll
            for (int i = 0; i < 8; i++) w[i] = mul2(w[i], r2);
            asm volatile("{ .reg .pred k; setp.ne.b32 k, %10, 0; @k st.shared.v4.b32 [%0], {%2,%3,%4,%5}; @k st.shared.v4.b32 [%1], {%6,%7,%8,%9}; }"
                :: "r"((addr ^ (32 * sg)) + 1024 * r), "r"((addr ^ (32 * sg + 16)) + 1024 * r), "r"(w[0]), "r"(w[1]), "r"(w[2]), "r"(w[3]),
                   "r"(w[4]), "r"(w[5]), "r"(w[6]), "r"(w[7]), "r"(keep & (1 << sg)) : "memory");
        }
        if ((keep == 2) | ((keep == 3) & (rs[0] > 0x1p-60f) & (rs[1] > 0x1p-60f) & (rs[2] > 0x1p-60f) & (rs[3] > 0x1p-60f))) break;
        keep = keep == 3 ? 1 : 2;
        const float sgn = keep == 1 ? 1.f : -1.f;
        float m0 = p[0] * sgn, m1 = p[2] * sgn;
        #pragma unroll
        for (int i = 0; i < 32; i++) { if (i & 2) m1 = fmaxf(m1, p[i] * sgn); else m0 = fmaxf(m0, p[i] * sgn); }
        #pragma unroll
        for (int i = 0; i < 32; i++) p[i] = fmaf((i & 2) ? m1 : m0, -sgn, p[i]);
    }
    __syncwarp();
}
__device__ __forceinline__ uint32_t gelu2(uint32_t h) {
    uint32_t u = mul2(h, fma2(mul2(h, h), 0x3E923E92u, 0x3FCC3FCCu));
    asm("tanh.approx.bf16x2 %0, %0;" : "+r"(u));
    return fma2(h, u, h);
}
__device__ __forceinline__ void pre_gelu(uint32_t (&o)[4], const float* a, uint32_t ba, uint32_t bb) {
    o[0] = fma2(pack2v(a[0], a[1]), 0x3F003F00u, ba); o[1] = fma2(pack2v(a[2], a[3]), 0x3F003F00u, ba);
    o[2] = fma2(pack2v(a[4], a[5]), 0x3F003F00u, bb); o[3] = fma2(pack2v(a[6], a[7]), 0x3F003F00u, bb);
}
__device__ __forceinline__ void gelu4(uint32_t (&o)[4]) { o[0] = gelu2(o[0]); o[1] = gelu2(o[1]); o[2] = gelu2(o[2]); o[3] = gelu2(o[3]); }
__device__ __forceinline__ void release(uint32_t sb, int s, int lane) {
    if (lane == 0) mbar_arrive(sb + OFF_BAR + (B_EMPTY + s) * 8);
}
__device__ __forceinline__ void wait_full(uint32_t sb, int s, int parity) { mbar_wait(sb + OFF_BAR + (B_FULL + s) * 8, parity); }

__device__ __forceinline__ void store_kv(const float (&kv)[20], uint32_t o, uint32_t zo, bool hi, int t) {
    #pragma unroll
    for (int nt = 0; nt < 2; nt++)
        sts128(o + nt * 512, __float_as_uint(hi ? kv[8 + 4 * nt] : kv[4 * nt]), __float_as_uint(hi ? kv[9 + 4 * nt] : kv[1 + 4 * nt]),
               __float_as_uint(hi ? kv[10 + 4 * nt] : kv[2 + 4 * nt]), __float_as_uint(hi ? kv[11 + 4 * nt] : kv[3 + 4 * nt]));
    if (t == 0) { sts32(zo, __float_as_uint(kv[16])); sts32(zo + 32, __float_as_uint(kv[18])); }
}
template <int N>
__device__ __forceinline__ void pack_tile(uint32_t (&p)[N][4], const float* acc, uint32_t tag) {
    #pragma unroll
    for (int i = 0; i < N; i++) {
        asm("lop3.b32 %0, %1, %2, 1, 0xD8;" : "=r"(p[i][0]) : "r"(pack2(acc[8 * i + 0], acc[8 * i + 1])), "r"(tag));
        p[i][1] = pack2(acc[8 * i + 2], acc[8 * i + 3]);
        p[i][2] = pack2(acc[8 * i + 4], acc[8 * i + 5]);
        p[i][3] = pack2(acc[8 * i + 6], acc[8 * i + 7]);
    }
}
__device__ __forceinline__ void stg128(uint4* dst, const uint32_t (&p)[4]) {
    asm volatile("st.relaxed.gpu.global.v4.b32 [%0], {%1,%2,%3,%4};" :: "l"(dst), "r"(p[0]), "r"(p[1]), "r"(p[2]), "r"(p[3]) : "memory");
}
__device__ __forceinline__ void set_flag(uint4* flag, int w, uint32_t fv, int lane) {
    if (lane == 0) asm volatile("st.relaxed.gpu.global.u32 [%0], %1;" :: "l"((uint32_t*)flag + w), "r"(fv) : "memory");
}
template <int N>
__device__ __forceinline__ void check_tile(uint32_t (&v)[N][4], const uint4* src, uint32_t tag) {
    while (true) {
        uint32_t bad = 0;
        #pragma unroll
        for (int i = 0; i < N; i++) asm("lop3.b32 %0, %0, %1, %2, 0xF6;" : "+r"(bad) : "r"(v[i][0]), "r"(tag));
        if (!__any_sync(0xffffffffu, bad & 1)) break;
        #pragma unroll
        for (int i = 0; i < N; i++)
            asm volatile("ld.relaxed.gpu.global.v4.b32 {%0,%1,%2,%3}, [%4];" : "=r"(v[i][0]), "=r"(v[i][1]), "=r"(v[i][2]), "=r"(v[i][3]) : "l"(src + i * 128) : "memory");
    }
}

#define MMA_STAGE(SPLIT, BODY)                                                             \
    wg_fence();                                                                            \
    _Pragma("unroll")                                                                      \
    for (int k = 0; k < 4; k++) {                                                          \
        const uint64_t d = dB + (uint64_t)((s * STB + k * 2048) >> 4);                     \
        BODY;                                                                              \
        if (SPLIT == 1 && s == 0 && k == 1) wg_commit();                                   \
        if (SPLIT == 2 && k == 1) { wg_commit(); wg_wait<1>(); }                           \
        if (SPLIT == 3 && k == 1) { wg_commit(); wg_wait<2>(); }                           \
    }                                                                                      \
    wg_commit()
#define STAGE_WAIT() wg_wait<1>()
#define G2_A(s, k) ((s) < 2 ? Ha[4 * ((s) & 1) + (k)] : (s) < 4 ? Pa[4 * ((s) & 1) + (k)] : (s) < 6 ? Hb[3 * ((s) & 1) + (k)] : Pb[3 * ((s) & 1) + (k)])
#define G2_HAS(s, k) ((k) < 3 || ((s) != 4 && (s) != 6))

__global__ void __cluster_dims__(2, 1, 1) __launch_bounds__(384, 1)
fused_kernel(const __grid_constant__ Params P) {
    extern __shared__ __align__(1024) uint8_t smem_raw[];
    const uint32_t sb = (uint32_t)__cvta_generic_to_shared(smem_raw);
    const int tid = threadIdx.x, warp = tid >> 5, lane = tid & 31;
    const int k0 = blockIdx.x >> 1, i7 = ((k0 - 36) * 37) >> 8;
    const int G = k0 < 4 ? 0 : k0 < 36 ? (k0 - 4) & 7 : k0 - 35 - 7 * i7, gi = k0 < 4 ? k0 : k0 < 36 ? (k0 - 4) >> 3 : i7;
    unsigned role = 16 * (G >> 1) + (k0 >= 4 && k0 < 36 ? 0 : 8) + 4 * (gi >> 1) + 2 * (G & 1) + (gi & 1);
    asm volatile("" : "+r"(role));
    const int m = (role >> 2) & 15, c = role & 3, r = blockIdx.x & 1, j = 2 * c + r, cc = c >> 1;
    if (tid < 256) TS(31);
    TG(41);
    const uint32_t bar = sb + OFF_BAR;

    if (warp >= 8) {
        asm volatile("setmaxnreg.dec.sync.aligned.u32 24;");
        if (warp == 8) {
            const bool el = elect_one();
            if (el) {
                #pragma unroll
                for (int i = 4; i < B_NUM; i++) mbar_init(bar + i * 8, i == B_MISC ? 3 : i < B_EMPTY ? 1 : i < B_XFREE ? 8 : i < B_KVRDY ? 4 : 2);
                #pragma unroll
                for (int i = B_RXA; i < B_RXFREE; i++) mbar_expect_tx(bar + i * 8, i < B_RXB ? 16384 : i < B_RXC ? 6144 : 8192);
                asm volatile("fence.mbarrier_init.release.cluster;" ::: "memory");
                TP(40);
            }
            __syncwarp();
            bar_arrive(0, 384);
            if (el) {
                #pragma unroll 1
                for (int i = 0; i < 4; i++) mbar_expect_tx(bar + (B_XFULL + 4 + i) * 8, STB);
            }
            __syncwarp();
            asm volatile("barrier.cluster.arrive.relaxed.aligned;" ::: "memory");
            if (el) {
                #pragma unroll 1
                for (int s = 0; s < X1_AT; s++) {
                    mbar_expect_tx(bar + (B_FULL + s) * 8, STB);
                    tma3d(sb + s * STB, &P.kv, 64 * j, 64 * s, 1, bar + (B_FULL + s) * 8);
                }
            }
            __syncwarp();
            if (X1_MC) asm volatile("barrier.cluster.wait.acquire.aligned;" ::: "memory");
            if (el) {
                if (X1_MC) {
                    #pragma unroll 1
                    for (int i = r; i < 4; i += 2)
                        asm volatile("cp.async.bulk.tensor.3d.shared::cluster.global.mbarrier::complete_tx::bytes.multicast::cluster [%0], [%1, {%3, %4, %5}], [%2], %6;"
                            :: "r"(sb + OFF_INC + i * STB), "l"(&P.x), "r"(bar + (B_XFULL + 4 + i) * 8), "r"(0), "r"(m * 128 + 64), "r"(2 * i), "h"((uint16_t)3) : "memory");
                } else {
                    #pragma unroll 1
                    for (int i = 0; i < 4; i++) tma3d(sb + OFF_INC + i * STB, &P.x, 0, m * 128 + 64, 2 * i, bar + (B_XFULL + 4 + i) * 8);
                }
                #pragma unroll 1
                for (int s = X1_AT; s < 4; s++) {
                    mbar_expect_tx(bar + (B_FULL + s) * 8, STB);
                    tma3d(sb + s * STB, &P.kv, 64 * j, 64 * s, 1, bar + (B_FULL + s) * 8);
                }
                if (m < 4) pf3d(&P.kv, 64 * j, 256 + 64 * m, 1);
            }
            if (el) {
                mbar_wait(bar + B_XFREE * 8, 0);
                #pragma unroll 1
                for (int s = 4; s < 8; s++) {
                    mbar_expect_tx(bar + (B_FULL + s) * 8, STB);
                    tma3d(sb + s * STB, &P.kv, 64 * j, 64 * s, 1, bar + (B_FULL + s) * 8);
                }
                if (PREFETCH) {
                    const int s = m & 7, jj = j ^ ((s >> 1) & 1), ch = 4 * r + 2 * (m >> 3);
                    if (m < 8) pf3d(&P.w1a, 176 * j, 64 * s, 0);
                    else { pf3d(&P.q, 64 * j, 64 * s, 0); pf3d(&P.w1b, 176 * j + 128, 64 * s, 0); }
                    mbar_wait(bar + (B_EMPTY + 0) * 8, 0);
                    if (s == 5 || s == 7) pf3d(&P.wo, 0, 64 * jj, ch);
                    else pf3d(&P.w2, 0, 176 * jj + (s < 4 ? 64 * (s & 1) : 128), ch);
                }
                #pragma unroll 1
                for (int s = 0; s < 8; s++) {
                    mbar_wait(bar + (B_EMPTY + s) * 8, 0);
                    mbar_expect_tx(bar + (B_FULL + s) * 8, STB);
                    tma3d(sb + s * STB, &P.w1a, 176 * j, 64 * s, 0, bar + (B_FULL + s) * 8);
                }
                #pragma unroll 1
                for (int s = 0; s < 8; s++) {
                    mbar_wait(bar + (B_EMPTY + s) * 8, 1);
                    mbar_expect_tx(bar + (B_FULL + s) * 8, STB);
                    tma3d(sb + s * STB, &P.q, 64 * j, 64 * s, 0, bar + (B_FULL + s) * 8);
                    tma3d(sb + s * STB + 8192, &P.w1b, 176 * j + 128, 64 * s, 0, bar + (B_FULL + s) * 8);
                }
                #pragma unroll 1
                for (int g = 0; g < 2; g++) {
                    mbar_wait(bar + (B_HAST + g) * 8, 0);
                    mbar_wait(bar + (B_RXFREE + g) * 8, 0);
                    const uint32_t dst = mapa(sb + OFF_INC + g * 32768, r ^ 1), rbar = mapa(bar + (B_RXA + g) * 8, r ^ 1);
                    asm volatile("cp.async.bulk.shared::cluster.shared::cta.mbarrier::complete_tx::bytes [%0], [%1], 8192, [%2];"
                        :: "r"(dst), "r"(sb + OFF_INC + g * 32768 + 16384), "r"(rbar) : "memory");
                    asm volatile("cp.async.bulk.shared::cluster.shared::cta.mbarrier::complete_tx::bytes [%0], [%1], 8192, [%2];"
                        :: "r"(dst + 8192), "r"(sb + OFF_XRES + g * 8192), "r"(rbar) : "memory");
                }
                #pragma unroll 1
                for (int s = 0; s < 8; s += 2) {
                    const int jj = j ^ ((s >> 1) & 1), ch = 4 * r + 2 * (cc ^ 1);
                    const uint32_t fb = bar + (B_FULL + s) * 8;
                    mbar_wait(bar + (B_EMPTY + s) * 8, 0);
                    mbar_expect_tx(fb, STB);
                    tma3d(sb + s * STB, &P.w2, 0, 176 * jj + 32 * (s & 4), ch, fb);
                    mbar_wait(bar + (B_EMPTY + s + 1) * 8, 0);
                    mbar_expect_tx(fb + 8, STB);
                    tma3d(sb + (s + 1) * STB, s < 4 ? &P.w2 : &P.wo, 0, s < 4 ? 176 * jj + 64 : 64 * jj, ch, fb + 8);
                }
                mbar_wait(bar + B_RXFREE2 * 8, 0); mbar_wait(bar + (B_RXFREE2 + 1) * 8, 0);
                mbar_expect_tx(bar + B_XRES * 8, STB);
                tma3d(sb + OFF_XRES, &P.xr, 0, m * 128, 4 * r + c, bar + B_XRES * 8);
                #pragma unroll 1
                for (int q = 0; q < 4; q++) {
                    const int jj = j ^ (q & 1), ch = 4 * r + (c ^ (q >> 1) ^ 1);
                    const uint32_t dst = q ? sb + (2 * q - 2) * STB : sb + OFF_INC, fb = bar + (B_FULLB + q) * 8;
                    if (q) mbar_wait(bar + (B_EMPTY + 2 * q - 2) * 8, 1); else mbar_wait(bar + B_PBDONE * 8, 0);
                    mbar_expect_tx(fb, 30720);
                    tma3d(dst, &P.w2h, 0, 176 * jj, ch, fb);
                    if (q) mbar_wait(bar + (B_EMPTY + 2 * q - 1) * 8, 1);
                    tma3d(dst + 11264, &P.w2h, 0, 176 * jj + 88, ch, fb);
                    tma3d(dst + 22528, &P.woh, 0, 64 * jj, ch, fb);
                }
            }
        } else if (warp == 11) {
            asm volatile("barrier.cluster.arrive.relaxed.aligned;" ::: "memory");
            if (lane == 0) asm volatile("prefetch.tensormap [%0];" :: "l"(&P.kv) : "memory");
            bar_sync(0, 384);
            if (lane < 9) {
                const CUtensorMap* tm = &P.q + lane;
                asm volatile("prefetch.tensormap [%0];" :: "l"(tm) : "memory");
            }
            if ((sb & 0x3FFFF) != SMEM_BASE) __trap();
            sts128(sb + OFF_ONES + lane * 16, ONES2, ONES2, ONES2, ONES2);
            sts128(sb + OFF_ONES + 512 + lane * 16, ONES2, ONES2, ONES2, ONES2);
            uint32_t bv[3];
            #pragma unroll
            for (int u = 0; u < 3; u++) bv[u] = (lane + 32 * u < 88 && 88 * j + lane + 32 * u < 688) ? __ldg((const uint32_t*)P.b1 + 88 * j + lane + 32 * u) : 0u;
            const uint32_t b2v = __ldg((const uint32_t*)(P.b2 + 256 * r + 64 * c) + lane);
            #pragma unroll
            for (int u = 0; u < 3; u++) {
                const int idx = lane + 32 * u;
                if (idx < 88) sts32(sb + OFF_B1 + (idx & 3) * 96 + (idx >> 2) * 4, mul2(bv[u], 0x3F003F00u));
            }
            sts32(sb + OFF_B2 + (lane & 3) * 32 + (lane >> 2) * 4, b2v);
            fence_async_smem();
            __syncwarp();
            if (lane == 0) {
                mbar_arrive(bar + B_MISC * 8);
            }
            if (lane == 0) {
                unsigned long long t0, t1;
                asm volatile("mov.u64 %0, %globaltimer;" : "=l"(t0));
                while (true) {
                    uint32_t ok;
                    asm volatile("{ .reg .pred p; mbarrier.try_wait.parity.shared::cta.b64 p, [%1], 0" WDHINT "; selp.u32 %0, 1, 0, p; }" : "=r"(ok) : "r"(bar + B_DONE * 8) : "memory");
                    if (ok) break;
                    asm volatile("mov.u64 %0, %globaltimer;" : "=l"(t1));
                    if (t1 - t0 > 2000000000ull) __trap();
                }
            }
        } else {
            const int g = warp - 9;
            asm volatile("barrier.cluster.arrive.relaxed.aligned;" ::: "memory");
            bar_sync(0, 384);
            unsigned ep;
            asm volatile("ld.relaxed.gpu.global.u32 %0, [%1];" : "=r"(ep) : "l"(&g_epoch) : "memory");
            {
                uint32_t v[8];
                #pragma unroll
                for (int u = 0; u < 8; u++) asm volatile("ld.global.nc.u32 %0, [%1];" : "=r"(v[u]) : "l"((const uint32_t*)P.wphi + j * 512 + g * 256 + u * 32 + lane) : "memory");
                #pragma unroll
                for (int u = 0; u < 8; u++) {
                    const int row = u * 4 + (lane >> 3);
                    const uint32_t wv = pack2(bflo(v[u]) * 1.4426950408889634f, bfhi(v[u]) * 1.4426950408889634f);
                    const uint32_t lo = g ? 0u : wv, hi = g ? wv : 0u;
                    sts128(sb + OFF_WBIG + g * 4096 + row * 128 + (((lane ^ row) & 7) << 4), u < 4 ? lo : 0u, u < 4 ? 0u : lo, u < 4 ? hi : 0u, u < 4 ? 0u : hi);
                }
                fence_async_smem();
                __syncwarp();
                if (lane == 0) mbar_arrive(bar + B_MISC * 8);
            }
            const float* kvg = g_kv[ep & 1][j];
            unsigned* cnt = &g_cnt[ep & 1][j][0];
            {
                float4* z = (float4*)&g_kv[(ep + 1) & 1][j][m * 136];
                if (lane < 17) z[g * 17 + lane] = make_float4(0.f, 0.f, 0.f, 0.f);
                if (m == 0 && lane == 0) g_cnt[(ep + 1) & 1][j][0] = 0;
            }
            asm volatile("barrier.cluster.wait.acquire.aligned;" ::: "memory");
            if (lane == 0) {
                sts32(sb + OFF_EP, ep);
                mbar_wait(bar + (B_KVST + g) * 8, 0);
                TSW(1 + g, 4);
                asm volatile("cp.reduce.async.bulk.global.shared::cta.bulk_group.add.f32 [%0], [%1], 8192;"
                    :: "l"(kvg), "r"(sb + OFF_INC + g * 32768 + R_KVP) : "memory");
                asm volatile("cp.reduce.async.bulk.global.shared::cta.bulk_group.add.f32 [%0], [%1], 512;"
                    :: "l"(kvg + 2048), "r"(sb + OFF_KVB + g * 512) : "memory");
                asm volatile("cp.async.bulk.commit_group;" ::: "memory");
                asm volatile("cp.async.bulk.wait_group.read 0;" ::: "memory");
                asm volatile("mbarrier.arrive.relaxed.cluster.shared::cluster.b64 _, [%0];" :: "r"(mapa(bar + (B_RXFREE + g) * 8, r ^ 1)) : "memory");
                asm volatile("cp.async.bulk.wait_group 0;" ::: "memory");
                TSW(1 + g, 0);
                asm volatile("red.relaxed.gpu.global.add.u32 [%0], 1;" :: "l"(cnt) : "memory");
                if (g == 1) {
                    unsigned v;
                    do { asm volatile("ld.relaxed.gpu.global.u32 %0, [%1];" : "=r"(v) : "l"(cnt) : "memory"); } while (v < 32);
                    TSW(1 + g, 1);
                    asm volatile("fence.proxy.async.global;" ::: "memory");
                    mbar_expect_tx(bar + B_KVRAW * 8, KV_FLOATS * 4);
                    asm volatile("cp.async.bulk.shared::cluster.global.mbarrier::complete_tx::bytes [%0], [%1], %2, [%3];"
                        :: "r"(sb + OFF_KVB), "l"(kvg), "r"(KV_FLOATS * 4), "r"(bar + B_KVRAW * 8) : "memory");
                }
            }
            __syncwarp();
            mbar_wait(bar + B_KVRAW * 8, 0);
            TSW(1 + g, 3);
            {
                uint32_t kb = sb + OFF_KVB + g * 4096 + lane * 16, zs = sb + OFF_KVB + 8192 + g * 256 + lane * 4;
                #pragma unroll 1
                for (int h = 0; h < 2; h++, kb += 2048, zs += 128) {
                    uint32_t w[8];
                    #pragma unroll
                    for (int u = 0; u < 4; u += 2) {
                        uint32_t v[4], y[4];
                        lds128(v, kb + u * 512); lds128(y, kb + u * 512 + 512);
                        w[2 * u] = pack2v(__uint_as_float(v[0]), __uint_as_float(v[1])); w[2 * u + 1] = pack2v(__uint_as_float(v[2]), __uint_as_float(v[3]));
                        w[2 * u + 2] = pack2v(__uint_as_float(y[0]), __uint_as_float(y[1])); w[2 * u + 3] = pack2v(__uint_as_float(y[2]), __uint_as_float(y[3]));
                    }
                    const float z = __uint_as_float(lds32(zs));
                    __syncwarp();
                    stsm4(kb, w[0], w[1], w[2], w[3]);
                    stsm4(kb + 768, w[4], w[5], w[6], w[7]);
                    const uint32_t zw = pack2(z, z);
                    sts128(kb + 512 + (lane >> 4) * 512, zw, zw, zw, zw);
                }
            }
            fence_async_smem();
            __syncwarp();
            if (lane == 0) mbar_arrive(bar + B_KVRDY * 8);
            TSW(1 + g, 2);
            const uint32_t* fp = (const uint32_t*)&g_flag[m * 8 + j][g * 3] + (lane < 12 ? lane : 0);
            const uint32_t xb = sb + (g ? OFF_INC + 40960 : OFF_WBIG);
            int state = 1;
            while (true) {
                uint32_t f;
                asm volatile("ld.relaxed.gpu.global.u32 %0, [%1];" : "=r"(f) : "l"(fp) : "memory");
                const uint32_t missing = __ballot_sync(0xffffffffu, f != ep + 1);
                #pragma unroll 1
                for (int late = 1; late >= 0; late--) {
                    if ((missing & (late ? 0xF : 0xFF0)) || (state & (2 << late))) continue;
                    state |= 2 << late;
                    if (lane == 0) TP(32 + 2 * late + g);
                    mbar_wait(bar + B_PBDONE * 8, 0);
                    mbar_wait(bar + (B_EMPTY + ((late | g) ? 7 : 0)) * 8, 1);
                    if (elect_one()) {
                        const uint32_t bytes = late ? 8192 : 16384, tbar = bar + (B_TILE + 2 * late + g) * 8;
                        mbar_expect_tx(tbar, bytes);
                        asm volatile("cp.async.bulk.shared::cluster.global.mbarrier::complete_tx::bytes [%0], [%1], %2, [%3];"
                            :: "r"(late ? sb + 6 * STB + g * 65536 : xb), "l"(g_part + (size_t)((m * 8 + j) * 8 + g * 3 + 1 - late) * 512), "r"(bytes), "r"(tbar) : "memory");
                    }
                    __syncwarp();
                }
                if (state == 7) break;
                if (QUIET) mbar_wait(bar + B_PBDONE * 8, 0);
            }
        }
    } else {
        const bool el0 = elect_one();
        if (warp == 1 || warp == 2) asm volatile("prefetch.global.L2 [%0];" :: "l"(P.xp + (m * 128 + 8 * j) * 512 + (tid - 32) * 64) : "memory");
        if (WPF && warp == 3 && lane < WPF) asm volatile("prefetch.global.L2 [%0];" :: "l"(P.wp + (m * (WPF / 2) + (lane >> 1)) * 1536 + 512 + 512 * (lane & 1) + 64 * j) : "memory");
        if (X1PF && (warp == 4 || warp == 5)) {
            const long long t0 = clock64();
            while (clock64() - t0 < X1PF) {}
            asm volatile("prefetch.global.L2 [%0];" :: "l"(P.xp + (m * 128 + 64 + 8 * j) * 512 + (tid - 128) * 64) : "memory");
        }
        if (el0 && warp == 0) {
            #pragma unroll
            for (int i = 0; i < 4; i++) mbar_init(bar + (B_XFULL + i) * 8, 1);
            asm volatile("fence.mbarrier_init.release.cluster;" ::: "memory");
            #pragma unroll
            for (int i = 0; i < 4; i++) {
                mbar_expect_tx(bar + (B_XFULL + i) * 8, STB);
                tma3d(sb + (4 + i) * STB, &P.x, 0, m * 128, 2 * i, bar + (B_XFULL + i) * 8);
            }
            TP(43);
        }
        __syncwarp();
        asm volatile("barrier.cluster.arrive.relaxed.aligned;" ::: "memory");
        asm volatile("setmaxnreg.inc.sync.aligned.u32 240;");
        bar_sync(0, 384);
        const int wg = __shfl_sync(0xffffffffu, warp >> 2, 0), w = warp & 3, t = lane & 3, g = lane >> 2, tw = tid & 127;
        const uint32_t reg = sb + OFF_INC + wg * 32768;
        if (wg < 2) TS(26);
        const int lrow = 16 * w + (lane & 15);
        const uint32_t swz = ((lane >> 4) ^ (lane & 7)) << 4;
        const uint32_t phia = reg + (t >> 1) * 8192 + (16 * w + g) * 128 + (((4 * (t & 1)) ^ (t & 2) ^ g) << 4);
        constexpr uint64_t dB = (uint64_t)(SMEM_BASE >> 4) | desc_hi(8192, 1024, 1);

        uint32_t A[32][4];
        {
            const uint32_t xst = sb + (wg ? OFF_INC : 4 * STB) + lrow * 128;
            #define LOADX(i) do { if (trip) mbar_wait(bar + (B_XFULL + 4 + (i)) * 8, 0); if ((i) == 0 || (i) == 3) TS((i) ? 25 : 24); \
                _Pragma("unroll") for (int k = 8 * (i); k < 8 * (i) + 8; k++) ldsm4(A[k], xst + (k >> 2) * 8192 + (swz ^ (32 * (k & 3)))); } while (0)
            uint32_t sc0, sc1, of0, of1;
            float base0 = 0.f, base1 = 0.f;
            int trip = WARM == 1 ? wg : WARM == 2 ? 1 - wg : 1;
            while (true) {
                float st[4];
                if (wg == 0) {
                    float s4[4][4], q4[4];
                    #pragma unroll
                    for (int i = 0; i < 4; i++) { s4[0][i] = 0.f; s4[1][i] = 0.f; s4[2][i] = 0.f; s4[3][i] = 0.f; q4[i] = 0.f; }
                    if (trip) mbar_wait(bar + B_XFULL * 8, 0);
                    #pragma unroll
                    for (int i = 0; i < 4; i++) {
                        if (i == 0 || !LPIPE) {
                            if (i && trip) mbar_wait(bar + (B_XFULL + i) * 8, 0);
                            if (i == 0 || i == 3) TS(i ? 25 : 24);
                            #pragma unroll
                            for (int k = 8 * i; k < 8 * i + 8; k++) ldsm4(A[k], xst + (k >> 2) * 8192 + (swz ^ (32 * (k & 3))));
                        }
                        if (i < 3 && LPIPE) {
                            if (trip) mbar_wait(bar + (B_XFULL + i + 1) * 8, 0);
                            if (i == 2) TS(25);
                            #pragma unroll
                            for (int k = 8 * i + 8; k < 8 * i + 16; k++) ldsm4(A[k], xst + (k >> 2) * 8192 + (swz ^ (32 * (k & 3))));
                        }
                        uint32_t c[4];
                        #pragma unroll
                        for (int k = 8 * i; k < 8 * i + 8; k++) {
                            mma_ones(s4[k & 3], A[k]);
                            #pragma unroll
                            for (int e = 0; e < 4; e++) c[e] = (k & 7) ? fma2(A[k][e], A[k][e], c[e]) : mul2(A[k][e], A[k][e]);
                        }
                        mma_ones(q4, c);
                    }
                    st[0] = (s4[0][0] + s4[1][0]) + (s4[2][0] + s4[3][0]); st[1] = (s4[0][2] + s4[1][2]) + (s4[2][2] + s4[3][2]); st[2] = q4[0]; st[3] = q4[2];
                } else {
                    uint32_t ps[4][4];
                    LOADX(0); LOADX(1); LOADX(2); LOADX(3);
                    #pragma unroll
                    for (int i = 0; i < 4; i++) stats8(A + 8 * i, ps[i]);
                    #pragma unroll
                    for (int i = 0; i < 4; i++) {
                        const uint32_t y = add2(ps[0][i], ps[1][i]), z = add2(ps[2][i], ps[3][i]);
                        st[i] = (bflo(y) + bfhi(y)) + (bflo(z) + bfhi(z));
                    }
                    #pragma unroll
                    for (int o = 1; o <= 2; o <<= 1) {
                        #pragma unroll
                        for (int i = 0; i < 4; i++) st[i] += __shfl_xor_sync(0xffffffffu, st[i], o);
                    }
                }
                const float mean0 = st[0] * (1.f / 512.f), mean1 = st[1] * (1.f / 512.f), q0 = st[2] * (1.f / 512.f), q1 = st[3] * (1.f / 512.f);
                const float var0 = fmaf(-mean0, mean0, q0), var1 = fmaf(-mean1, mean1, q1);
                const float rs0 = rsq(fmaxf(var0, 0.f) + 1e-5f), rs1 = rsq(fmaxf(var1, 0.f) + 1e-5f);
                const uint32_t mb = pack2(base0 + mean0, base1 + mean1);
                sc0 = pack2(rs0, rs0); sc1 = pack2(rs1, rs1);
                const float d0 = (base0 - bflo(mb)) * bflo(sc0), d1 = (base1 - bfhi(mb)) * bflo(sc1);
                of0 = pack2(d0, d0); of1 = pack2(d1, d1);
                const bool redo = __any_sync(0xffffffffu, !(var0 >= 0.5f * q0) || !(var1 >= 0.5f * q1) || (of0 & of1) == 0xFFFFFFFFu);
                if (trip == 2 || (trip == 1 && !redo)) break;
                if (trip == 1) {
                    base0 = bflo(mb); base1 = bfhi(mb);
                    const uint32_t m0 = pack2(base0, base0), m1 = pack2(base1, base1);
                    #pragma unroll 1
                    for (int k = 0; k < 32; k++) {
                        const uint32_t a = xst + (k >> 2) * 8192 + (swz ^ (32 * (k & 3)));
                        uint32_t v[4];
                        ldsm4(v, a);
                        stsm4(a, sub2(v[0], m0), sub2(v[1], m1), sub2(v[2], m0), sub2(v[3], m1));
                    }
                    fence_async_smem();
                    __syncwarp();
                }
                trip++;
            }
            if (lane == 0) mbar_arrive(bar + (B_XFREE + wg) * 8);
            TS(0);
            norm4(A, sc0, sc1, of0, of1);
            if (NORM_UP && wg < 2) {
                #pragma unroll
                for (int u = 1; u < NORM_UP; u++) norm4(A + 4 * u, sc0, sc1, of0, of1);
            }
            TS(29);
            if (wg == 1) bar_sync(6, 256);
            float acc[64];
            #pragma unroll
            for (int s = 0; s < 8; s++) {
                if (s == 0) wait_full(sb, 0, 0);
                MMA_STAGE((s >= 3 ? SPLIT1 : SPLIT0), if (s == 0 && k == 0) wgmma_rs128_first(acc, A[0], d); else wgmma_rs128(acc, A[4 * s + k], d));
                if (s == 0) TS(1);
                if (s == PP_STAGE) bar_arrive(6 - wg, 256);
                if (s > 1) release(sb, s - 2, lane);
                if (s < 7) wait_full(sb, s + 1, 0);
                TSS(0, s);
                if (s < 7 && s + 1 >= NORM_UP) norm4(A + 4 * s + 4, sc0, sc1, of0, of1);
                if (s > 0 || SPLIT0) STAGE_WAIT();
                if (s == 7) release(sb, 6, lane);
            }
            mbar_wait(bar + B_MISC * 8, 0);
            wg_wait<0>();
            release(sb, 7, lane);
            TS(2);

            float p[32];
            uint32_t ka[4][4];
            logits_issue(acc, ka, p);
            mbar_wait(bar + (B_XFREE + 1) * 8, 0);
            if (!VPIN || wg < 2) {
                const uint32_t va = reg + R_V + lrow * 64 + (((lane >> 4) ^ ((lane >> 1) & 3)) << 4);
                #pragma unroll
                for (int h = 0; h < 4; h++) {
                    const float* v = acc + 32 + 8 * h;
                    stsm4((va ^ (32 * (h & 1))) + (h >> 1) * 4096, pack2v(v[0], v[1]), pack2v(v[2], v[3]), pack2v(v[4], v[5]), pack2v(v[6], v[7]));
                }
            }
            wg_wait<0>();
            TS(19);
            features(p, phia);
            TS(3);
            fence_async_smem();
            bar_sync(1 + wg, 128);
            float kv0[20], kv1[20];
            wg_fence();
            kv_mma(kv0, kv1, wg);
            const uint32_t kvo = reg + R_KVP + lane * 16, zo = sb + OFF_KVB + wg * 512 + (w * 16 + g) * 4;
            wg_wait<1>();
            store_kv(kv0, kvo + w * 1024, zo, w >> 1, t);
            wg_wait<0>();
            TS(16);
            store_kv(kv1, kvo + 4096 + (w ^ 1) * 1024, (zo ^ 64) + 256, w >> 1, t);
            if (KV_EARLY == 1 || (KV_EARLY == 2 && wg == 1)) {
                fence_async_smem();
                __syncwarp();
                if (lane == 0) mbar_arrive(bar + (B_KVST + wg) * 8);
            }
        }
        TS(4);
        const uint32_t rreg = mapa(reg + tw * 16, r ^ 1);
        const uint32_t park = sb + OFF_XRES + wg * 8192 + tw * 16;
        uint32_t Ha[8][4];
        {
            float acc[64];
            bar_sync(5 + wg, 256);
            #pragma unroll
            for (int s = 0; s < 8; s++) {
                if (s == 0) wait_full(sb, 0, 1);
                MMA_STAGE((s >= 3 ? SPLIT1 : SPLIT0), if (s == 0 && k == 0) wgmma_rs128_first(acc, A[0], d); else wgmma_rs128(acc, A[4 * s + k], d));
                if (s == 0) TS(20);
                if (s == PP_STAGE) bar_arrive(6 - wg, 256);
                if (s > 1) release(sb, s - 2, lane);
                if (s < 7) wait_full(sb, s + 1, 1);
                TSS(1, s);
                if (s == 1 && (KV_EARLY == 0 || (KV_EARLY == 2 && wg == 0))) {
                    fence_async_smem();
                    __syncwarp();
                    if (lane == 0) mbar_arrive(bar + (B_KVST + wg) * 8);
                }
                if (s > 0 || SPLIT0) STAGE_WAIT();
                if (s == 7) release(sb, 6, lane);
            }
            uint32_t bw[4][4];
            #pragma unroll
            for (int i = 0; i < 4; i++) lds128(bw[i], sb + OFF_B1 + t * 96 + i * 16);
            wg_wait<0>();
            release(sb, 7, lane);
            TS(5);
            #pragma unroll
            for (int i = 7; i >= 0; i--) {
                pre_gelu(Ha[i], acc + 8 * i, bw[i >> 1][2 * (i & 1)], bw[i >> 1][2 * (i & 1) + 1]);
                gelu4(Ha[i]);
                sts128(i >= 4 ? park + (i - 4) * 2048 : reg + tw * 16 + (8 + i) * 2048, Ha[i][0], Ha[i][1], Ha[i][2], Ha[i][3]);
            }
            fence_async_smem();
            __syncwarp();
            if (lane == 0) mbar_arrive(bar + (B_HAST + wg) * 8);
        }
        TS(6);
        uint32_t Hb[7][4];
        uint32_t Pa[8][4], Pb[7][4];
        {
            float acc[56];
            bar_sync(5 + wg, 256);
            #pragma unroll
            for (int s = 0; s < 8; s++) {
                if (s == 0) wait_full(sb, 0, 0);
                MMA_STAGE(SPLIT0, if (s == 0 && k == 0) wgmma_rs112_first(acc, A[0], d); else wgmma_rs112(acc, A[4 * s + k], d));
                if (s == 0) TS(21);
                if (s == PP_STAGE) bar_arrive(6 - wg, 256);
                if (s > 1) release(sb, s - 2, lane);
                if (s < 7) wait_full(sb, s + 1, 0);
                TSS(2, s);
                if (s >= 2 && s < 6) {
                    #pragma unroll
                    for (int i = 2 * s - 4; i < 2 * s - 2; i++) lds128(Ha[i], i < 4 ? reg + tw * 16 + (8 + i) * 2048 : park + (i - 4) * 2048);
                }
                if (s == PA_AT) mbar_wait(bar + (B_RXA + wg) * 8, 0);
                if (s >= PA_AT) {
                    #pragma unroll
                    for (int i = (s - PA_AT) * 8 / (8 - PA_AT); i < (s + 1 - PA_AT) * 8 / (8 - PA_AT); i++) lds128(Pa[i], reg + i * 2048 + tw * 16);
                }
                if (s > 0 || SPLIT0) STAGE_WAIT();
                if (s == 7) release(sb, 6, lane);
            }
            wg_wait<0>();
            release(sb, 7, lane);
            TS(7);
            float p[32];
            uint32_t qa[4][4];
            logits_issue(acc, qa, p);
            bar_sync(1 + wg, 128);
            if (tw == 0) asm volatile("mbarrier.arrive.relaxed.cluster.shared::cluster.b64 _, [%0];" :: "r"(mapa(bar + (B_RXFREE2 + wg) * 8, r ^ 1)) : "memory");
            uint32_t bw[2][4];
            lds128(bw[0], sb + OFF_B1 + t * 96 + 64); lds128(bw[1], sb + OFF_B1 + t * 96 + 80);
            #pragma unroll
            for (int i = 0; i < 3; i++) pre_gelu(Hb[i], acc + 32 + 8 * i, bw[i >> 1][2 * (i & 1)], bw[i >> 1][2 * (i & 1) + 1]);
            if (wg < 2) { gelu4(Hb[0]); gelu4(Hb[1]); gelu4(Hb[2]); }
            wg_wait<0>();
            TS(17);
            features(p, phia);
            TS(8);
            fence_async_smem();
            if (wg >= HB_LATE) {
                mbar_wait(bar + (B_RXFREE2 + wg) * 8, 0);
                const uint32_t rbar = mapa(bar + (B_RXB + wg) * 8, r ^ 1);
                #pragma unroll
                for (int i = 0; i < 3; i++) st_async4(rreg + (8 + i) * 2048, Hb[i], rbar);
            }
            mbar_wait(bar + B_KVRDY * 8, 0);
            TS(9);
        }
        const unsigned ep = lds32(sb + OFF_EP);
        const uint32_t tag = (ep + 1) & 1;
        #define PART(o) (g_part + (size_t)((m * 8 + 2 * (o) + r) * 8 + wg * 3 + (c ^ (o)) - 1) * 512 + tw)
        #define FLAG(o) (&g_flag[m * 8 + 2 * (o) + r][wg * 3 + (c ^ (o)) - 1])
        const uint32_t xb = sb + (wg ? OFF_INC + 40960 : OFF_WBIG) + tw * 16;
        float own[32];
        {
            float o[4][12], acc[64];
            bar_sync(5 + wg, 256);
            wg_fence();
            readout_mma(o, wg);
            wg_commit();
            #pragma unroll
            for (int s = 0; s < 8; s++) {
                if (s == 0) wait_full(sb, 0, 1);
                MMA_STAGE(false, if (s == 0 && k == 0) wgmma_rs128_first(acc, Ha[0], d); else if (G2_HAS(s, k)) wgmma_rs128(acc, G2_A(s, k), d));
                if (s == 0) TS(22);
                if (s == PP_STAGE) bar_arrive(6 - wg, 256);
                if (s > 1) release(sb, s - 2, lane);
                if (s < 7) wait_full(sb, s + 1, 1);
                TSS(3, s);
                if (s == 0 && wg < HB_LATE) {
                    mbar_wait(bar + (B_RXFREE2 + wg) * 8, 0);
                    const uint32_t rbar = mapa(bar + (B_RXB + wg) * 8, r ^ 1);
                    #pragma unroll
                    for (int i = 0; i < 3; i++) st_async4(rreg + (8 + i) * 2048, Hb[i], rbar);
                }
                if (s == 1) {
                    wg_wait<2>();
                    const uint32_t rbar = mapa(bar + (B_RXC + wg) * 8, r ^ 1);
                    #pragma unroll
                    for (int h = 0; h < 4; h++) {
                        const float r0 = rcp(o[h][8] + 1e-6f), r1 = rcp(o[h][10] + 1e-6f);
                        Hb[3 + h][0] = pack2(o[h][0] * r0, o[h][1] * r0); Hb[3 + h][1] = pack2(o[h][2] * r1, o[h][3] * r1);
                        Hb[3 + h][2] = pack2(o[h][4] * r0, o[h][5] * r0); Hb[3 + h][3] = pack2(o[h][6] * r1, o[h][7] * r1);
                        st_async4(rreg + (11 + h) * 2048, Hb[3 + h], rbar);
                    }
                    TS(10);
                }
                if (s == 4) {
                    mbar_wait(bar + (B_RXB + wg) * 8, 0);
                    #pragma unroll
                    for (int i = 0; i < 3; i++) lds128(Pb[i], reg + (8 + i) * 2048 + tw * 16);
                }
                if (s == 5) {
                    mbar_wait(bar + (B_RXC + wg) * 8, 0);
                    #pragma unroll
                    for (int i = 3; i < 7; i++) lds128(Pb[i], reg + (8 + i) * 2048 + tw * 16);
                }
                if (s == 7 && wg == 0 && lane == 0) mbar_arrive(bar + B_PBDONE * 8);
                if (s > 0) STAGE_WAIT();
                if (s == 7) release(sb, 6, lane);
            }
            wg_wait<0>();
            release(sb, 7, lane);
            TS(11);
            uint32_t pk[8][4];
            pack_tile(pk, acc, tag);
            mbar_wait(bar + (B_EMPTY + STORE_GATE) * 8, 1);
            #pragma unroll
            for (int i = 0; i < 8; i++) {
                const int oc = 2 * (cc ^ 1) + (i >> 2);
                stg128(PART(oc) + (i & 3) * 128, pk[i]);
                if ((i & 3) == 3) set_flag(FLAG(oc), w, ep + 1, lane);
            }
            TS(12);
        }
        const uint32_t tb = sb + 6 * STB + wg * 65536;
        const uint4* const mine = g_part + (size_t)((m * 8 + j) * 8 + wg * 3) * 512 + tw;
        uint32_t xv[4][4];
        #pragma unroll
        for (int hf = 0; hf < 2; hf++) {
            float oth[32];
            mbar_wait(bar + (B_FULLB + 2 * hf) * 8, 0);
            bar_sync(5 + wg, 256);
            #pragma unroll
            for (int n = 0; n < 8; n++) {
                const int s = (n & 1) | ((n & 2) << 1) | ((n & 4) >> 1);
                if (n == 4) mbar_wait(bar + (B_FULLB + 2 * hf + 1) * 8, 0);
                if (n == 0 || n == 4) wg_fence();
                #pragma unroll
                for (int k = 0; k < 4; k++) {
                    const int q = 2 * hf + ((s >> 1) & 1);
                    const uint64_t d = dB + (((q ? (2 * q - 2) * STB : OFF_INC) + (s < 4 ? (s & 1) * 8192 : (s & 1) ? 22528 : 16384) + k * 2048) >> 4);
                    if (hf == 0) { if (s == 0 && k == 0) wgmma_rs64_first(oth, Ha[0], d); else if (G2_HAS(s, k)) wgmma_rs64(oth, G2_A(s, k), d); }
                    else { if (s == 0 && k == 0) wgmma_rs64_first(own, Ha[0], d); else if (G2_HAS(s, k)) wgmma_rs64(own, G2_A(s, k), d); }
                }
                if (s == 0) TS(hf ? 27 : 23);
                TSS(4 + hf, s);
                if (s == PPB_STAGE && (hf & wg) == 0) bar_arrive(6 - wg, 256);
                if (s == 7) wg_commit();
            }
            if (hf == 0) {
                wg_wait<0>();
                TS(13);
                uint32_t pk[4][4];
                pack_tile(pk, oth, tag);
                #pragma unroll
                for (int i = 0; i < 4; i++) stg128(PART(c ^ 1) + i * 128, pk[i]);
                set_flag(FLAG(c ^ 1), w, ep + 1, lane);
                TS(30);
                mbar_wait(bar + B_XRES * 8, 0);
                uint32_t bw[2][4];
                lds128(bw[0], sb + OFF_B2 + t * 32); lds128(bw[1], sb + OFF_B2 + t * 32 + 16);
                #pragma unroll
                for (int i = 0; i < 4; i++) ldsm4(xv[i], sb + OFF_XRES + wg * 8192 + lrow * 128 + (swz ^ (32 * i)));
                if (wg < 2) {
                    #pragma unroll
                    for (int i = 0; i < 16; i++) xv[i >> 2][i & 3] = add2(xv[i >> 2][i & 3], bw[i >> 3][(i >> 1) & 3]);
                }
            }
        }
        {
            uint32_t ost = tb + 24576 + w * 2048, oa = ost + (lane & 15) * 128 + swz;
            {
                uint32_t u[8][4];
                mbar_wait(bar + (B_TILE + wg) * 8, 0);
                #pragma unroll
                for (int i = 0; i < 8; i++) lds128(u[i], xb + i * 2048);
                check_tile(u, mine + 512, tag);
                #pragma unroll
                for (int i = 0; i < 16; i++) xv[i >> 2][i & 3] = add2(add2(u[i >> 2][i & 3], xv[i >> 2][i & 3]), u[4 + (i >> 2)][i & 3]);
            }
            wg_wait<0>();
            if (wg < 2) {
                #pragma unroll
                for (int i = 0; i < 16; i++) {
                    if (FINP == 2) xv[i >> 2][i & 3] = add2(xv[i >> 2][i & 3], pack2(own[2 * i], own[2 * i + 1]));
                    else {
                        own[2 * i] += bflo(xv[i >> 2][i & 3]); own[2 * i + 1] += bfhi(xv[i >> 2][i & 3]);
                        if (FINP) xv[i >> 2][i & 3] = pack2(own[2 * i], own[2 * i + 1]);
                    }
                }
            }
            TS(18);
            uint32_t v[4][4];
            mbar_wait(bar + (B_TILE + 2 + wg) * 8, 0);
            #pragma unroll
            for (int i = 0; i < 4; i++) lds128(v[i], tb + tw * 16 + i * 2048);
            check_tile(v, mine, tag);
            if (lane == 0) mbar_arrive(bar + B_DONE * 8);
            TS(14);
            #pragma unroll
            for (int i = 0; i < 4; i++) {
                uint32_t o[4];
                #pragma unroll
                for (int e = 0; e < 4; e++)
                    o[e] = FINP ? add2(xv[i][e], v[i][e]) : pack2(own[8 * i + 2 * e] + bflo(v[i][e]), own[8 * i + 2 * e + 1] + bfhi(v[i][e]));
                stsm4(oa ^ (32 * i), o[0], o[1], o[2], o[3]);
            }
            TS(28);
            __syncwarp();
            uint4* op = (uint4*)P.outp + (size_t)(m * 128 + wg * 64 + 16 * w + (lane >> 3)) * 64 + (4 * r + c) * 8 + (lane & 7);
            #pragma unroll
            for (int i = 0; i < 4; i++) lds128(v[i], ((ost + (lane >> 3) * 128 + (((lane ^ (lane >> 3)) & 7) << 4)) ^ ((i & 1) * 64)) + i * 512);
            #pragma unroll
            for (int i = 0; i < 4; i++) op[i * 256] = make_uint4(v[i][0], v[i][1], v[i][2], v[i][3]);
            if (blockIdx.x == 0 && tid == 128) asm volatile("st.relaxed.gpu.global.u32 [%0], %1;" :: "l"(&g_epoch), "r"(ep + 1) : "memory");
        }
        TS(15);
        TSDUMP();
    }
}

typedef CUresult (*EncFn)(CUtensorMap*, CUtensorMapDataType, cuuint32_t, void*, const cuuint64_t*, const cuuint64_t*, const cuuint32_t*,
                          const cuuint32_t*, CUtensorMapInterleave, CUtensorMapSwizzle, CUtensorMapL2promotion, CUtensorMapFloatOOBfill);

void encode(EncFn enc, CUtensorMap* tm, const void* base, int rank, cuuint64_t d0, cuuint64_t d1, cuuint64_t d2, cuuint64_t s1, cuuint64_t s2,
            cuuint32_t b0, cuuint32_t b1, cuuint32_t b2) {
    cuuint64_t gd[3] = {d0, d1, d2}, gs[2] = {s1, s2};
    cuuint32_t bd[3] = {b0, b1, b2}, es[3] = {1, 1, 1};
    enc(tm, CU_TENSOR_MAP_DATA_TYPE_BFLOAT16, rank, const_cast<void*>(base), gd, gs, bd, es, CU_TENSOR_MAP_INTERLEAVE_NONE,
        CU_TENSOR_MAP_SWIZZLE_128B, PROMO, CU_TENSOR_MAP_FLOAT_OOB_FILL_NONE);
}

}

extern "C" void kernel_launch(void* const* d_in, const int* in_sizes, int n_in, void* d_out, int out_size) {
    (void)in_sizes; (void)n_in; (void)out_size;
    static EncFn enc = nullptr;
    if (!enc) {
        void* fn = nullptr;
        cudaDriverEntryPointQueryResult qr;
        cudaGetDriverEntryPoint("cuTensorMapEncodeTiled", &fn, cudaEnableDefault, &qr);
        enc = (EncFn)fn;
        cudaFuncSetAttribute(fused_kernel, cudaFuncAttributeMaxDynamicSharedMemorySize, LAUNCH_SMEM);
    }
    Params P;
    encode(enc, &P.x, d_in[0], 3, 64, 2048, 8, 1024, 128, 64, 64, 2);
    encode(enc, &P.kv, d_in[1], 3, 512, 512, 3, 3072, 1024, 64, 64, 2);
    encode(enc, &P.q, d_in[1], 3, 512, 512, 3, 3072, 1024, 64, 64, 1);
    encode(enc, &P.w1a, d_in[5], 3, 1376, 512, 2, 2752, 128, 64, 64, 2);
    encode(enc, &P.w1b, d_in[5], 3, 1376, 512, 2, 2752, 128, 64, 64, 1);
    encode(enc, &P.w2h, d_in[7], 3, 64, 1376, 8, 1024, 128, 64, 88, 1);
    encode(enc, &P.woh, d_in[3], 3, 64, 512, 8, 1024, 128, 64, 64, 1);
    encode(enc, &P.w2, d_in[7], 3, 64, 1376, 8, 1024, 128, 64, 64, 2);
    encode(enc, &P.wo, d_in[3], 3, 64, 512, 8, 1024, 128, 64, 64, 2);
    encode(enc, &P.out, d_out, 3, 64, 2048, 8, 1024, 128, 64, 16, 1);
    encode(enc, &P.xr, d_in[0], 3, 64, 2048, 8, 1024, 128, 64, 128, 1);
    P.outp = d_out;
    P.xp = (const __nv_bfloat16*)d_in[0];
    P.wp = (const __nv_bfloat16*)d_in[1];
    P.wphi = (const __nv_bfloat16*)d_in[2];
    P.b1 = (const __nv_bfloat16*)d_in[6];
    P.b2 = (const __nv_bfloat16*)d_in[8];
    fused_kernel<<<128, 384, LAUNCH_SMEM, cudaStreamPerThread>>>(P);
}
```

```cpp
#include <cuda_runtime.h>
#include <cuda_bf16.h>
#include <cuda.h>
#include <stdint.h>


namespace {

constexpr uint32_t SMEM_BASE = 1024;
constexpr int NST = 8;
constexpr int STB = 16384;
constexpr int OFF_INC = NST * STB;
constexpr int OFF_SPARE = OFF_INC + 65536;
constexpr int OFF_WBIG = OFF_SPARE + 16384;
constexpr int OFF_ONES = OFF_WBIG + 8192;
constexpr int OFF_KVB = OFF_ONES + 1024;
constexpr int OFF_B1 = OFF_KVB + 8704;
constexpr int OFF_B2 = OFF_B1 + 384;
constexpr int OFF_EP = OFF_B2 + 128;
constexpr int OFF_BAR = OFF_EP + 16;
enum { B_XFULL = 0, B_FULL = 8, B_RXA = 19, B_RXB = 21, B_RXC = 23, B_RXFREE = 25, B_MISC = 27, B_XRES = 28, B_KVRAW = 29, B_RXFREE2 = 30, B_FULLB = 32, B_TILE = 36,
       B_KVRD = 40, B_EMPTY = 42, B_DONE = 50, B_XFREE = 51, B_KVST = 53, B_PBDONE = 55, B_HAST = 56, B_KVRDY = 58, B_NUM = 59 };
constexpr int SMEM_BYTES = OFF_BAR + B_NUM * 8;
static_assert(SMEM_BYTES <= 232448, "smem");
constexpr int R_KVP = 24576;
constexpr int R_V = 16384;
constexpr int KV_FLOATS = 2176;

__device__ __align__(128) float g_kv[2][8][KV_FLOATS];
__device__ __align__(128) unsigned g_cnt[2][8][32];
__device__ unsigned g_epoch;
__device__ __align__(128) uint4 g_flag[128][8];
__device__ uint4 g_part[128 * 8 * 512];

struct Params {
    CUtensorMap x, kv, q, w1a, w1b, w2, wo, xr, w2h, woh;
    const __nv_bfloat16* wphi;
    const __nv_bfloat16* b1;
    const __nv_bfloat16* b2;
    void* outp;
    const __nv_bfloat16* xp;
};

__device__ __forceinline__ void mbar_init(uint32_t bar, uint32_t cnt) { asm volatile("mbarrier.init.shared::cta.b64 [%0], %1;" :: "r"(bar), "r"(cnt) : "memory"); }
__device__ __forceinline__ void mbar_expect_tx(uint32_t bar, uint32_t bytes) { asm volatile("mbarrier.arrive.expect_tx.shared::cta.b64 _, [%0], %1;" :: "r"(bar), "r"(bytes) : "memory"); }
__device__ __forceinline__ void mbar_arrive(uint32_t bar) { asm volatile("mbarrier.arrive.shared::cta.b64 _, [%0];" :: "r"(bar) : "memory"); }
__device__ __forceinline__ void mbar_wait(uint32_t bar, uint32_t parity) {
    asm volatile("{\n"
        ".reg .pred p;\n"
        "WL%=:\n"
        "mbarrier.try_wait.parity.shared::cta.b64 p, [%0], %1;\n"
        "@!p bra WL%=;\n"
        "}" :: "r"(bar), "r"(parity) : "memory");
}
__device__ __forceinline__ void tma3d(uint32_t dst, const CUtensorMap* tm, int c0, int c1, int c2, uint32_t bar) {
    asm volatile("cp.async.bulk.tensor.3d.shared::cluster.global.mbarrier::complete_tx::bytes [%0], [%1, {%3, %4, %5}], [%2];"
        :: "r"(dst), "l"(tm), "r"(bar), "r"(c0), "r"(c1), "r"(c2) : "memory");
}
__device__ __forceinline__ void pf3d(const CUtensorMap* tm, int c0, int c1, int c2) {
    asm volatile("cp.async.bulk.prefetch.tensor.3d.L2.global [%0, {%1, %2, %3}];" :: "l"(tm), "r"(c0), "r"(c1), "r"(c2) : "memory");
}
__device__ __forceinline__ bool elect_one() {
    uint32_t p;
    asm volatile("{ .reg .pred P; elect.sync _|P, 0xffffffff; selp.u32 %0, 1, 0, P; }" : "=r"(p));
    return p;
}
__device__ __forceinline__ void wg_fence() { asm volatile("wgmma.fence.sync.aligned;" ::: "memory"); }
__device__ __forceinline__ void wg_commit() { asm volatile("wgmma.commit_group.sync.aligned;" ::: "memory"); }
template <int N> __device__ __forceinline__ void wg_wait() { asm volatile("wgmma.wait_group.sync.aligned %0;" :: "n"(N) : "memory"); }
__device__ __forceinline__ void fence_async_smem() { asm volatile("fence.proxy.async.shared::cta;" ::: "memory"); }
__device__ __forceinline__ void bar_sync(int id, int n) { asm volatile("bar.sync %0, %1;" :: "r"(id), "r"(n) : "memory"); }
__device__ __forceinline__ void bar_arrive(int id, int n) { asm volatile("bar.arrive %0, %1;" :: "r"(id), "r"(n) : "memory"); }
__device__ __forceinline__ void ldsm4(uint32_t (&r)[4], uint32_t addr) {
    asm volatile("ldmatrix.sync.aligned.m8n8.x4.shared.b16 {%0,%1,%2,%3}, [%4];" : "=r"(r[0]), "=r"(r[1]), "=r"(r[2]), "=r"(r[3]) : "r"(addr) : "memory");
}
__device__ __forceinline__ void stsm4(uint32_t addr, uint32_t a, uint32_t b, uint32_t c, uint32_t d) {
    asm volatile("stmatrix.sync.aligned.m8n8.x4.shared.b16 [%0], {%1,%2,%3,%4};" :: "r"(addr), "r"(a), "r"(b), "r"(c), "r"(d) : "memory");
}
__device__ __forceinline__ void lds128(uint32_t (&r)[4], uint32_t addr) {
    asm volatile("ld.shared.v4.b32 {%0,%1,%2,%3}, [%4];" : "=r"(r[0]), "=r"(r[1]), "=r"(r[2]), "=r"(r[3]) : "r"(addr) : "memory");
}
__device__ __forceinline__ uint32_t lds32(uint32_t addr) { uint32_t r; asm volatile("ld.shared.b32 %0, [%1];" : "=r"(r) : "r"(addr) : "memory"); return r; }
__device__ __forceinline__ void sts128(uint32_t addr, uint32_t a, uint32_t b, uint32_t c, uint32_t d) {
    asm volatile("st.shared.v4.b32 [%0], {%1,%2,%3,%4};" :: "r"(addr), "r"(a), "r"(b), "r"(c), "r"(d) : "memory");
}
__device__ __forceinline__ void sts32(uint32_t addr, uint32_t a) { asm volatile("st.shared.b32 [%0], %1;" :: "r"(addr), "r"(a) : "memory"); }
__device__ __forceinline__ void st_async4(uint32_t addr, const uint32_t (&v)[4], uint32_t bar) {
    asm volatile("st.async.weak.shared::cluster.mbarrier::complete_tx::bytes.v4.b32 [%0], {%1,%2,%3,%4}, [%5];"
        :: "r"(addr), "r"(v[0]), "r"(v[1]), "r"(v[2]), "r"(v[3]), "r"(bar) : "memory");
}
__device__ __forceinline__ uint32_t mapa(uint32_t addr, uint32_t cta) { uint32_t r; asm("mapa.shared::cluster.u32 %0, %1, %2;" : "=r"(r) : "r"(addr), "r"(cta)); return r; }
__device__ __forceinline__ void mma_ones(float (&d)[4], const uint32_t (&a)[4]) {
    asm("mma.sync.aligned.m16n8k16.row.col.f32.bf16.bf16.f32 {%0,%1,%2,%3}, {%4,%5,%6,%7}, {%8,%8}, {%0,%1,%2,%3};"
        : "+f"(d[0]), "+f"(d[1]), "+f"(d[2]), "+f"(d[3]) : "r"(a[0]), "r"(a[1]), "r"(a[2]), "r"(a[3]), "r"(0x3F803F80u));
}
__device__ __forceinline__ uint32_t add2(uint32_t a, uint32_t b) { uint32_t r; asm("add.rn.bf16x2 %0, %1, %2;" : "=r"(r) : "r"(a), "r"(b)); return r; }
__device__ __forceinline__ uint32_t pack2(float lo, float hi) { uint32_t r; asm("cvt.rn.bf16x2.f32 %0, %1, %2;" : "=r"(r) : "f"(hi), "f"(lo)); return r; }
__device__ __forceinline__ uint32_t pack2v(float lo, float hi) { uint32_t r; asm volatile("cvt.rn.bf16x2.f32 %0, %1, %2;" : "=r"(r) : "f"(hi), "f"(lo)); return r; }
__device__ __forceinline__ float bflo(uint32_t w) { return __uint_as_float(w << 16); }
__device__ __forceinline__ float bfhi(uint32_t w) { return __uint_as_float(w & 0xffff0000u); }
__device__ __forceinline__ float rcp(float x) { float r; asm("rcp.approx.ftz.f32 %0, %1;" : "=f"(r) : "f"(x)); return r; }
__device__ __forceinline__ float rsq(float x) { float r; asm("rsqrt.approx.ftz.f32 %0, %1;" : "=f"(r) : "f"(x)); return r; }
__device__ __forceinline__ uint32_t sub2(uint32_t a, uint32_t b) { uint32_t r; asm("sub.rn.bf16x2 %0, %1, %2;" : "=r"(r) : "r"(a), "r"(b)); return r; }
__device__ __forceinline__ void wgmma_rs128_first(float (&d)[64], const uint32_t (&a)[4], uint64_t db) {
    asm volatile("{ .reg .pred p; setp.ne.b32 p, 0, 0; wgmma.mma_async.sync.aligned.m64n128k16.f32.bf16.bf16 "
        "{%0,%1,%2,%3,%4,%5,%6,%7,%8,%9,%10,%11,%12,%13,%14,%15,%16,%17,%18,%19,%20,%21,%22,%23,%24,%25,%26,%27,%28,%29,%30,%31,%32,%33,%34,%35,%36,%37,%38,%39,%40,%41,%42,%43,%44,%45,%46,%47,%48,%49,%50,%51,%52,%53,%54,%55,%56,%57,%58,%59,%60,%61,%62,%63}, {%64,%65,%66,%67}, %68, p, 1, 1, 1; }"
        : "=f"(d[0]),"=f"(d[1]),"=f"(d[2]),"=f"(d[3]),"=f"(d[4]),"=f"(d[5]),"=f"(d[6]),"=f"(d[7]),"=f"(d[8]),"=f"(d[9]),"=f"(d[10]),"=f"(d[11]),"=f"(d[12]),"=f"(d[13]),"=f"(d[14]),"=f"(d[15]),"=f"(d[16]),"=f"(d[17]),"=f"(d[18]),"=f"(d[19]),"=f"(d[20]),"=f"(d[21]),"=f"(d[22]),"=f"(d[23]),"=f"(d[24]),"=f"(d[25]),"=f"(d[26]),"=f"(d[27]),"=f"(d[28]),"=f"(d[29]),"=f"(d[30]),"=f"(d[31]),"=f"(d[32]),"=f"(d[33]),"=f"(d[34]),"=f"(d[35]),"=f"(d[36]),"=f"(d[37]),"=f"(d[38]),"=f"(d[39]),"=f"(d[40]),"=f"(d[41]),"=f"(d[42]),"=f"(d[43]),"=f"(d[44]),"=f"(d[45]),"=f"(d[46]),"=f"(d[47]),"=f"(d[48]),"=f"(d[49]),"=f"(d[50]),"=f"(d[51]),"=f"(d[52]),"=f"(d[53]),"=f"(d[54]),"=f"(d[55]),"=f"(d[56]),"=f"(d[57]),"=f"(d[58]),"=f"(d[59]),"=f"(d[60]),"=f"(d[61]),"=f"(d[62]),"=f"(d[63])
        : "r"(a[0]), "r"(a[1]), "r"(a[2]), "r"(a[3]), "l"(db));
}
__device__ __forceinline__ void wgmma_rs128(float (&d)[64], const uint32_t (&a)[4], uint64_t db) {
    asm volatile("{ .reg .pred p; setp.ne.b32 p, 1, 0; wgmma.mma_async.sync.aligned.m64n128k16.f32.bf16.bf16 "
        "{%0,%1,%2,%3,%4,%5,%6,%7,%8,%9,%10,%11,%12,%13,%14,%15,%16,%17,%18,%19,%20,%21,%22,%23,%24,%25,%26,%27,%28,%29,%30,%31,%32,%33,%34,%35,%36,%37,%38,%39,%40,%41,%42,%43,%44,%45,%46,%47,%48,%49,%50,%51,%52,%53,%54,%55,%56,%57,%58,%59,%60,%61,%62,%63}, {%64,%65,%66,%67}, %68, p, 1, 1, 1; }"
        : "+f"(d[0]),"+f"(d[1]),"+f"(d[2]),"+f"(d[3]),"+f"(d[4]),"+f"(d[5]),"+f"(d[6]),"+f"(d[7]),"+f"(d[8]),"+f"(d[9]),"+f"(d[10]),"+f"(d[11]),"+f"(d[12]),"+f"(d[13]),"+f"(d[14]),"+f"(d[15]),"+f"(d[16]),"+f"(d[17]),"+f"(d[18]),"+f"(d[19]),"+f"(d[20]),"+f"(d[21]),"+f"(d[22]),"+f"(d[23]),"+f"(d[24]),"+f"(d[25]),"+f"(d[26]),"+f"(d[27]),"+f"(d[28]),"+f"(d[29]),"+f"(d[30]),"+f"(d[31]),"+f"(d[32]),"+f"(d[33]),"+f"(d[34]),"+f"(d[35]),"+f"(d[36]),"+f"(d[37]),"+f"(d[38]),"+f"(d[39]),"+f"(d[40]),"+f"(d[41]),"+f"(d[42]),"+f"(d[43]),"+f"(d[44]),"+f"(d[45]),"+f"(d[46]),"+f"(d[47]),"+f"(d[48]),"+f"(d[49]),"+f"(d[50]),"+f"(d[51]),"+f"(d[52]),"+f"(d[53]),"+f"(d[54]),"+f"(d[55]),"+f"(d[56]),"+f"(d[57]),"+f"(d[58]),"+f"(d[59]),"+f"(d[60]),"+f"(d[61]),"+f"(d[62]),"+f"(d[63])
        : "r"(a[0]), "r"(a[1]), "r"(a[2]), "r"(a[3]), "l"(db));
}
__device__ __forceinline__ void wgmma_rs112_first(float (&d)[56], const uint32_t (&a)[4], uint64_t db) {
    asm volatile("{ .reg .pred p; setp.ne.b32 p, 0, 0; wgmma.mma_async.sync.aligned.m64n112k16.f32.bf16.bf16 "
        "{%0,%1,%2,%3,%4,%5,%6,%7,%8,%9,%10,%11,%12,%13,%14,%15,%16,%17,%18,%19,%20,%21,%22,%23,%24,%25,%26,%27,%28,%29,%30,%31,%32,%33,%34,%35,%36,%37,%38,%39,%40,%41,%42,%43,%44,%45,%46,%47,%48,%49,%50,%51,%52,%53,%54,%55}, {%56,%57,%58,%59}, %60, p, 1, 1, 1; }"
        : "=f"(d[0]),"=f"(d[1]),"=f"(d[2]),"=f"(d[3]),"=f"(d[4]),"=f"(d[5]),"=f"(d[6]),"=f"(d[7]),"=f"(d[8]),"=f"(d[9]),"=f"(d[10]),"=f"(d[11]),"=f"(d[12]),"=f"(d[13]),"=f"(d[14]),"=f"(d[15]),"=f"(d[16]),"=f"(d[17]),"=f"(d[18]),"=f"(d[19]),"=f"(d[20]),"=f"(d[21]),"=f"(d[22]),"=f"(d[23]),"=f"(d[24]),"=f"(d[25]),"=f"(d[26]),"=f"(d[27]),"=f"(d[28]),"=f"(d[29]),"=f"(d[30]),"=f"(d[31]),"=f"(d[32]),"=f"(d[33]),"=f"(d[34]),"=f"(d[35]),"=f"(d[36]),"=f"(d[37]),"=f"(d[38]),"=f"(d[39]),"=f"(d[40]),"=f"(d[41]),"=f"(d[42]),"=f"(d[43]),"=f"(d[44]),"=f"(d[45]),"=f"(d[46]),"=f"(d[47]),"=f"(d[48]),"=f"(d[49]),"=f"(d[50]),"=f"(d[51]),"=f"(d[52]),"=f"(d[53]),"=f"(d[54]),"=f"(d[55])
        : "r"(a[0]), "r"(a[1]), "r"(a[2]), "r"(a[3]), "l"(db));
}
__device__ __forceinline__ void wgmma_rs112(float (&d)[56], const uint32_t (&a)[4], uint64_t db) {
    asm volatile("{ .reg .pred p; setp.ne.b32 p, 1, 0; wgmma.mma_async.sync.aligned.m64n112k16.f32.bf16.bf16 "
        "{%0,%1,%2,%3,%4,%5,%6,%7,%8,%9,%10,%11,%12,%13,%14,%15,%16,%17,%18,%19,%20,%21,%22,%23,%24,%25,%26,%27,%28,%29,%30,%31,%32,%33,%34,%35,%36,%37,%38,%39,%40,%41,%42,%43,%44,%45,%46,%47,%48,%49,%50,%51,%52,%53,%54,%55}, {%56,%57,%58,%59}, %60, p, 1, 1, 1; }"
        : "+f"(d[0]),"+f"(d[1]),"+f"(d[2]),"+f"(d[3]),"+f"(d[4]),"+f"(d[5]),"+f"(d[6]),"+f"(d[7]),"+f"(d[8]),"+f"(d[9]),"+f"(d[10]),"+f"(d[11]),"+f"(d[12]),"+f"(d[13]),"+f"(d[14]),"+f"(d[15]),"+f"(d[16]),"+f"(d[17]),"+f"(d[18]),"+f"(d[19]),"+f"(d[20]),"+f"(d[21]),"+f"(d[22]),"+f"(d[23]),"+f"(d[24]),"+f"(d[25]),"+f"(d[26]),"+f"(d[27]),"+f"(d[28]),"+f"(d[29]),"+f"(d[30]),"+f"(d[31]),"+f"(d[32]),"+f"(d[33]),"+f"(d[34]),"+f"(d[35]),"+f"(d[36]),"+f"(d[37]),"+f"(d[38]),"+f"(d[39]),"+f"(d[40]),"+f"(d[41]),"+f"(d[42]),"+f"(d[43]),"+f"(d[44]),"+f"(d[45]),"+f"(d[46]),"+f"(d[47]),"+f"(d[48]),"+f"(d[49]),"+f"(d[50]),"+f"(d[51]),"+f"(d[52]),"+f"(d[53]),"+f"(d[54]),"+f"(d[55])
        : "r"(a[0]), "r"(a[1]), "r"(a[2]), "r"(a[3]), "l"(db));
}
__device__ __forceinline__ void wgmma_rs64_first(float (&d)[32], const uint32_t (&a)[4], uint64_t db) {
    asm volatile("{ .reg .pred p; setp.ne.b32 p, 0, 0; wgmma.mma_async.sync.aligned.m64n64k16.f32.bf16.bf16 "
        "{%0,%1,%2,%3,%4,%5,%6,%7,%8,%9,%10,%11,%12,%13,%14,%15,%16,%17,%18,%19,%20,%21,%22,%23,%24,%25,%26,%27,%28,%29,%30,%31}, {%32,%33,%34,%35}, %36, p, 1, 1, 1; }"
        : "=f"(d[0]),"=f"(d[1]),"=f"(d[2]),"=f"(d[3]),"=f"(d[4]),"=f"(d[5]),"=f"(d[6]),"=f"(d[7]),"=f"(d[8]),"=f"(d[9]),"=f"(d[10]),"=f"(d[11]),"=f"(d[12]),"=f"(d[13]),"=f"(d[14]),"=f"(d[15]),"=f"(d[16]),"=f"(d[17]),"=f"(d[18]),"=f"(d[19]),"=f"(d[20]),"=f"(d[21]),"=f"(d[22]),"=f"(d[23]),"=f"(d[24]),"=f"(d[25]),"=f"(d[26]),"=f"(d[27]),"=f"(d[28]),"=f"(d[29]),"=f"(d[30]),"=f"(d[31])
        : "r"(a[0]), "r"(a[1]), "r"(a[2]), "r"(a[3]), "l"(db));
}
__device__ __forceinline__ void wgmma_rs64(float (&d)[32], const uint32_t (&a)[4], uint64_t db) {
    asm volatile("{ .reg .pred p; setp.ne.b32 p, 1, 0; wgmma.mma_async.sync.aligned.m64n64k16.f32.bf16.bf16 "
        "{%0,%1,%2,%3,%4,%5,%6,%7,%8,%9,%10,%11,%12,%13,%14,%15,%16,%17,%18,%19,%20,%21,%22,%23,%24,%25,%26,%27,%28,%29,%30,%31}, {%32,%33,%34,%35}, %36, p, 1, 1, 1; }"
        : "+f"(d[0]),"+f"(d[1]),"+f"(d[2]),"+f"(d[3]),"+f"(d[4]),"+f"(d[5]),"+f"(d[6]),"+f"(d[7]),"+f"(d[8]),"+f"(d[9]),"+f"(d[10]),"+f"(d[11]),"+f"(d[12]),"+f"(d[13]),"+f"(d[14]),"+f"(d[15]),"+f"(d[16]),"+f"(d[17]),"+f"(d[18]),"+f"(d[19]),"+f"(d[20]),"+f"(d[21]),"+f"(d[22]),"+f"(d[23]),"+f"(d[24]),"+f"(d[25]),"+f"(d[26]),"+f"(d[27]),"+f"(d[28]),"+f"(d[29]),"+f"(d[30]),"+f"(d[31])
        : "r"(a[0]), "r"(a[1]), "r"(a[2]), "r"(a[3]), "l"(db));
}
template <uint32_t AHI, uint32_t BHI>
__device__ __forceinline__ void wgmma_ss40_first(float (&d)[20], uint32_t alo, uint32_t blo) {
    asm volatile("{ .reg .pred p; .reg .b64 da, db; setp.ne.b32 p, 0, 0; mov.b64 da, {%20, %22}; mov.b64 db, {%21, %23}; "
        "wgmma.mma_async.sync.aligned.m64n40k16.f32.bf16.bf16 "
        "{%0,%1,%2,%3,%4,%5,%6,%7,%8,%9,%10,%11,%12,%13,%14,%15,%16,%17,%18,%19}, da, db, p, 1, 1, 1, 1; }"
        : "=f"(d[0]),"=f"(d[1]),"=f"(d[2]),"=f"(d[3]),"=f"(d[4]),"=f"(d[5]),"=f"(d[6]),"=f"(d[7]),"=f"(d[8]),"=f"(d[9]),"=f"(d[10]),"=f"(d[11]),"=f"(d[12]),"=f"(d[13]),"=f"(d[14]),"=f"(d[15]),"=f"(d[16]),"=f"(d[17]),"=f"(d[18]),"=f"(d[19])
        : "r"(alo), "r"(blo), "n"(AHI), "n"(BHI));
}
template <uint32_t AHI, uint32_t BHI>
__device__ __forceinline__ void wgmma_ss40(float (&d)[20], uint32_t alo, uint32_t blo) {
    asm volatile("{ .reg .pred p; .reg .b64 da, db; setp.ne.b32 p, 1, 0; mov.b64 da, {%20, %22}; mov.b64 db, {%21, %23}; "
        "wgmma.mma_async.sync.aligned.m64n40k16.f32.bf16.bf16 "
        "{%0,%1,%2,%3,%4,%5,%6,%7,%8,%9,%10,%11,%12,%13,%14,%15,%16,%17,%18,%19}, da, db, p, 1, 1, 1, 1; }"
        : "+f"(d[0]),"+f"(d[1]),"+f"(d[2]),"+f"(d[3]),"+f"(d[4]),"+f"(d[5]),"+f"(d[6]),"+f"(d[7]),"+f"(d[8]),"+f"(d[9]),"+f"(d[10]),"+f"(d[11]),"+f"(d[12]),"+f"(d[13]),"+f"(d[14]),"+f"(d[15]),"+f"(d[16]),"+f"(d[17]),"+f"(d[18]),"+f"(d[19])
        : "r"(alo), "r"(blo), "n"(AHI), "n"(BHI));
}
template <uint32_t AHI, uint32_t BHI>
__device__ __forceinline__ void wgmma_ss24_first(float (&d)[12], uint32_t alo, uint32_t blo) {
    asm volatile("{ .reg .pred p; .reg .b64 da, db; setp.ne.b32 p, 0, 0; mov.b64 da, {%12, %14}; mov.b64 db, {%13, %15}; "
        "wgmma.mma_async.sync.aligned.m64n24k16.f32.bf16.bf16 "
        "{%0,%1,%2,%3,%4,%5,%6,%7,%8,%9,%10,%11}, da, db, p, 1, 1, 0, 1; }"
        : "=f"(d[0]),"=f"(d[1]),"=f"(d[2]),"=f"(d[3]),"=f"(d[4]),"=f"(d[5]),"=f"(d[6]),"=f"(d[7]),"=f"(d[8]),"=f"(d[9]),"=f"(d[10]),"=f"(d[11])
        : "r"(alo), "r"(blo), "n"(AHI), "n"(BHI));
}
template <uint32_t AHI, uint32_t BHI>
__device__ __forceinline__ void wgmma_ss24(float (&d)[12], uint32_t alo, uint32_t blo) {
    asm volatile("{ .reg .pred p; .reg .b64 da, db; setp.ne.b32 p, 1, 0; mov.b64 da, {%12, %14}; mov.b64 db, {%13, %15}; "
        "wgmma.mma_async.sync.aligned.m64n24k16.f32.bf16.bf16 "
        "{%0,%1,%2,%3,%4,%5,%6,%7,%8,%9,%10,%11}, da, db, p, 1, 1, 0, 1; }"
        : "+f"(d[0]),"+f"(d[1]),"+f"(d[2]),"+f"(d[3]),"+f"(d[4]),"+f"(d[5]),"+f"(d[6]),"+f"(d[7]),"+f"(d[8]),"+f"(d[9]),"+f"(d[10]),"+f"(d[11])
        : "r"(alo), "r"(blo), "n"(AHI), "n"(BHI));
}


constexpr uint32_t ONES2 = 0x3F803F80u;

__device__ __forceinline__ uint32_t fma2(uint32_t a, uint32_t b, uint32_t c) { uint32_t r; asm("fma.rn.bf16x2 %0, %1, %2, %3;" : "=r"(r) : "r"(a), "r"(b), "r"(c)); return r; }
__device__ __forceinline__ uint32_t mul2(uint32_t a, uint32_t b) { uint32_t r; asm("mul.rn.bf16x2 %0, %1, %2;" : "=r"(r) : "r"(a), "r"(b)); return r; }
__device__ __forceinline__ void norm4(uint32_t (*A)[4], uint32_t s0, uint32_t s1, uint32_t o0, uint32_t o1) {
    #pragma unroll
    for (int k = 0; k < 4; k++) { A[k][0] = fma2(A[k][0], s0, o0); A[k][1] = fma2(A[k][1], s1, o1); A[k][2] = fma2(A[k][2], s0, o0); A[k][3] = fma2(A[k][3], s1, o1); }
}
__device__ __forceinline__ void stats8(const uint32_t (*A)[4], uint32_t (&o)[4]) {
    uint32_t c[8], q[4];
    #pragma unroll
    for (int i = 0; i < 8; i++) c[i] = add2(add2(A[i & 4][i & 3], A[(i & 4) + 1][i & 3]), add2(A[(i & 4) + 2][i & 3], A[(i & 4) + 3][i & 3]));
    #pragma unroll
    for (int k = 0; k < 8; k++) {
        #pragma unroll
        for (int i = 0; i < 4; i++) q[i] = k ? fma2(A[k][i], A[k][i], q[i]) : mul2(A[k][i], A[k][i]);
    }
    o[0] = add2(add2(c[0], c[4]), add2(c[2], c[6])); o[1] = add2(add2(c[1], c[5]), add2(c[3], c[7]));
    o[2] = add2(q[0], q[2]); o[3] = add2(q[1], q[3]);
}
__host__ __device__ constexpr uint64_t desc_hi(uint32_t lbo, uint32_t sbo, uint32_t swz) { return ((uint64_t)(lbo >> 4) << 16) | ((uint64_t)(sbo >> 4) << 32) | ((uint64_t)swz << 62); }

__device__ __forceinline__ void logits_issue(const float* acc, uint32_t (&a)[4][4], float (&p)[32]) {
    constexpr uint64_t dW = (uint64_t)((SMEM_BASE + OFF_WBIG) >> 4) | desc_hi(8192, 1024, 1);
    #pragma unroll
    for (int h = 0; h < 4; h++) {
        const float* k = acc + 8 * h;
        a[h][0] = pack2(k[0], k[1]); a[h][1] = pack2(k[2], k[3]); a[h][2] = pack2(k[4], k[5]); a[h][3] = pack2(k[6], k[7]);
    }
    wg_fence();
    #pragma unroll
    for (int h = 0; h < 4; h++) { if (h == 0) wgmma_rs64_first(p, a[0], dW); else wgmma_rs64(p, a[h], dW + h * 128); }
    wg_commit();
}
__device__ __forceinline__ void kv_mma(float (&kv0)[20], float (&kv1)[20], uint32_t wg) {
    constexpr uint32_t base = SMEM_BASE + OFF_INC, AHI = (uint32_t)(desc_hi(0, 1024, 1) >> 32), BHI = (uint32_t)(desc_hi(0, 512, 2) >> 32);
    const uint32_t oa = wg * 2048, ob = wg * (2048u - (2048u << 16));
    #pragma unroll
    for (int hp = 0; hp < 2; hp++) {
        #pragma unroll
        for (int ks = 0; ks < 4; ks++) {
            const uint32_t vb = base + R_V + hp * 4096 + ks * 1024;
            const uint32_t a = oa + (((base + hp * 8192 + ks * 2048) >> 4) | (512u << 16));
            const uint32_t b = ob + ((vb >> 4) | (((SMEM_BASE + OFF_ONES - vb) >> 4) << 16));
            if (hp == 0) { if (ks == 0) wgmma_ss40_first<AHI, BHI>(kv0, a, b); else wgmma_ss40<AHI, BHI>(kv0, a, b); }
            else { if (ks == 0) wgmma_ss40_first<AHI, BHI>(kv1, a, b); else wgmma_ss40<AHI, BHI>(kv1, a, b); }
        }
        wg_commit();
    }
}
__device__ __forceinline__ void readout_mma(float (&o)[4][12], uint32_t wg) {
    constexpr uint32_t base = SMEM_BASE + OFF_INC, AHI = (uint32_t)(desc_hi(0, 1024, 1) >> 32), BHI = (uint32_t)(desc_hi(0, 256, 0) >> 32);
    const uint32_t oa = wg * 2048;
    #pragma unroll
    for (int h = 0; h < 4; h++) {
        #pragma unroll
        for (int sg = 0; sg < 2; sg++) {
            const uint32_t a = oa + (((base + (h >> 1) * 8192 + 32 * ((2 * (h & 1) + sg) ^ (h >> 1))) >> 4) | (1u << 16));
            const uint32_t b = ((SMEM_BASE + OFF_KVB + h * 2048 + sg * 768) >> 4) | (8u << 16);
            if (sg == 0) wgmma_ss24_first<AHI, BHI>(o[h], a, b); else wgmma_ss24<AHI, BHI>(o[h], a, b);
        }
    }
}
__device__ __forceinline__ void features(float (&p)[32], uint32_t addr) {
    int trip = 0;
    while (true) {
        bool ok = true;
        float e[2][16], tt[2][8];
        #pragma unroll
        for (int r = 0; r < 2; r++) {
            #pragma unroll
            for (int i = 0; i < 16; i++) asm volatile("ex2.approx.ftz.f32 %0, %1;" : "=f"(e[r][i]) : "f"(p[4 * (i >> 1) + 2 * r + (i & 1)]));
            #pragma unroll
            for (int i = 0; i < 8; i++) asm volatile("ex2.approx.ftz.f32 %0, %1;" : "=f"(tt[r][i]) : "f"(-(p[4 * i + 2 * r] + p[4 * i + 2 * r + 1])));
        }
        #pragma unroll
        for (int r = 0; r < 2; r++) {
            float s[8];
            const float* t = tt[r];
            uint32_t w[8], y[8];
            #pragma unroll
            for (int i = 0; i < 8; i++) { s[i] = e[r][2 * i] + e[r][2 * i + 1]; w[i] = pack2(e[r][2 * i], e[r][2 * i + 1]); }
            const float rp = rcp(((s[0] + s[1]) + (s[2] + s[3])) + ((s[4] + s[5]) + (s[6] + s[7])));
            const float rm = rcp(fmaf(s[0], t[0], fmaf(s[1], t[1], fmaf(s[2], t[2], s[3] * t[3]))) + fmaf(s[4], t[4], fmaf(s[5], t[5], fmaf(s[6], t[6], s[7] * t[7]))));
            const uint32_t r2 = pack2(rp, rp);
            #pragma unroll
            for (int i = 0; i < 8; i += 2) {
                const uint32_t c = pack2(t[i] * rm, t[i + 1] * rm);
                asm("{ .reg .b16 l, h; .reg .b32 x, z; mov.b32 {l, h}, %4; mov.b32 x, {l, l}; mov.b32 z, {h, h}; mul.rn.bf16x2 %0, %2, x; mul.rn.bf16x2 %1, %3, z; }"
                    : "=r"(y[i]), "=r"(y[i + 1]) : "r"(w[i]), "r"(w[i + 1]), "r"(c));
            }
            sts128(addr + 1024 * r, mul2(w[0], r2), mul2(w[1], r2), mul2(w[2], r2), mul2(w[3], r2));
            sts128((addr ^ 16) + 1024 * r, mul2(w[4], r2), mul2(w[5], r2), mul2(w[6], r2), mul2(w[7], r2));
            asm volatile("{ .reg .pred k; setp.eq.b32 k, %10, 0; @k st.shared.v4.b32 [%0], {%2,%3,%4,%5}; @k st.shared.v4.b32 [%1], {%6,%7,%8,%9}; }"
                :: "r"((addr ^ 32) + 1024 * r), "r"((addr ^ 48) + 1024 * r), "r"(y[0]), "r"(y[1]), "r"(y[2]), "r"(y[3]),
                   "r"(y[4]), "r"(y[5]), "r"(y[6]), "r"(y[7]), "r"(trip) : "memory");
            ok = ok & (rp > 0x1p-40f) & (rm > 0x1p-40f);
        }
        if ((trip == 2) | ((trip == 0) & ok)) break;
        if (trip == 1) {
            #pragma unroll
            for (int i = 0; i < 32; i += 2) { const float a = p[i]; p[i] = -p[i + 1]; p[i + 1] = -a; }
            addr ^= 32;
        }
        float m0 = p[0], m1 = p[2];
        #pragma unroll
        for (int i = 0; i < 32; i++) { if (i & 2) m1 = fmaxf(m1, p[i]); else m0 = fmaxf(m0, p[i]); }
        #pragma unroll
        for (int i = 0; i < 32; i++) p[i] -= (i & 2) ? m1 : m0;
        trip++;
    }
    __syncwarp();
}
__device__ __forceinline__ uint32_t gelu2(uint32_t h) {
    uint32_t u = mul2(h, fma2(mul2(h, h), 0x3E923E92u, 0x3FCC3FCCu));
    asm("tanh.approx.bf16x2 %0, %0;" : "+r"(u));
    return fma2(h, u, h);
}
__device__ __forceinline__ void pre_gelu(uint32_t (&o)[4], const float* a, uint32_t ba, uint32_t bb) {
    o[0] = fma2(pack2v(a[0], a[1]), 0x3F003F00u, ba); o[1] = fma2(pack2v(a[2], a[3]), 0x3F003F00u, ba);
    o[2] = fma2(pack2v(a[4], a[5]), 0x3F003F00u, bb); o[3] = fma2(pack2v(a[6], a[7]), 0x3F003F00u, bb);
}
__device__ __forceinline__ void gelu4(uint32_t (&o)[4]) { o[0] = gelu2(o[0]); o[1] = gelu2(o[1]); o[2] = gelu2(o[2]); o[3] = gelu2(o[3]); }
__device__ __forceinline__ void release(uint32_t sb, int s, int lane) {
    if (lane == 0) mbar_arrive(sb + OFF_BAR + (B_EMPTY + s) * 8);
}
__device__ __forceinline__ void wait_full(uint32_t sb, int s, int pass) { mbar_wait(sb + OFF_BAR + (B_FULL + (s < 7 ? s : 7 + pass)) * 8, s < 7 ? pass & 1 : 0); }

__device__ __forceinline__ void store_kv(const float (&kv)[20], uint32_t o, uint32_t zo, bool hi, int t) {
    #pragma unroll
    for (int nt = 0; nt < 2; nt++)
        sts128(o + nt * 512, __float_as_uint(hi ? kv[8 + 4 * nt] : kv[4 * nt]), __float_as_uint(hi ? kv[9 + 4 * nt] : kv[1 + 4 * nt]),
               __float_as_uint(hi ? kv[10 + 4 * nt] : kv[2 + 4 * nt]), __float_as_uint(hi ? kv[11 + 4 * nt] : kv[3 + 4 * nt]));
    if (t == 0) { sts32(zo, __float_as_uint(kv[16])); sts32(zo + 32, __float_as_uint(kv[18])); }
}
template <int N>
__device__ __forceinline__ void pack_tile(uint32_t (&p)[N][4], const float* acc, uint32_t tag) {
    #pragma unroll
    for (int i = 0; i < N; i++) {
        asm("lop3.b32 %0, %1, %2, 1, 0xD8;" : "=r"(p[i][0]) : "r"(pack2(acc[8 * i + 0], acc[8 * i + 1])), "r"(tag));
        p[i][1] = pack2(acc[8 * i + 2], acc[8 * i + 3]);
        p[i][2] = pack2(acc[8 * i + 4], acc[8 * i + 5]);
        p[i][3] = pack2(acc[8 * i + 6], acc[8 * i + 7]);
    }
}
__device__ __forceinline__ void stg128(uint4* dst, const uint32_t (&p)[4]) {
    asm volatile("st.relaxed.gpu.global.v4.b32 [%0], {%1,%2,%3,%4};" :: "l"(dst), "r"(p[0]), "r"(p[1]), "r"(p[2]), "r"(p[3]) : "memory");
}
__device__ __forceinline__ void set_flag(uint4* flag, int w, uint32_t fv, int lane) {
    if (lane == 0) asm volatile("st.relaxed.gpu.global.u32 [%0], %1;" :: "l"((uint32_t*)flag + w), "r"(fv) : "memory");
}
template <int N>
__device__ __forceinline__ void check_tile(uint32_t (&v)[N][4], const uint4* src, uint32_t tag) {
    while (true) {
        uint32_t bad = 0;
        #pragma unroll
        for (int i = 0; i < N; i++) asm("lop3.b32 %0, %0, %1, %2, 0xF6;" : "+r"(bad) : "r"(v[i][0]), "r"(tag));
        if (!__any_sync(0xffffffffu, bad & 1)) break;
        #pragma unroll
        for (int i = 0; i < N; i++)
            asm volatile("ld.relaxed.gpu.global.v4.b32 {%0,%1,%2,%3}, [%4];" : "=r"(v[i][0]), "=r"(v[i][1]), "=r"(v[i][2]), "=r"(v[i][3]) : "l"(src + i * 128) : "memory");
    }
}

#define MMA_STAGE(PASS, SPLIT, BODY)                                                       \
    if (s == 0) wait_full(sb, 0, PASS);                                                    \
    wg_fence();                                                                            \
    _Pragma("unroll")                                                                      \
    for (int k = 0; k < 4; k++) {                                                          \
        const uint64_t d = dB + (uint64_t)(((s == 7 && ((PASS) & 1) ? OFF_SPARE : s * STB) + k * 2048) >> 4); \
        BODY;                                                                              \
        if (SPLIT && s == 0 && k == 1) wg_commit();                                        \
    }                                                                                      \
    wg_commit();                                                                           \
    if (s == 7) bar_arrive(6 - wg, 256);                    \
    if (s > 1) release(sb, s - 2, lane);                                                   \
    if (s < 7) wait_full(sb, s + 1, PASS)
#define STAGE_END(SPLIT)                                                                   \
    if (s > 0 || SPLIT) wg_wait<1>();                                                      \
    if (s == 7) release(sb, 6, lane)
#define G2_A(s, k) ((s) < 2 ? Ha[4 * ((s) & 1) + (k)] : (s) < 4 ? Pa[4 * ((s) & 1) + (k)] : (s) < 6 ? Hb[3 * ((s) & 1) + (k)] : Pb[3 * ((s) & 1) + (k)])
#define G2_HAS(s, k) ((k) < 3 || ((s) != 4 && (s) != 6))

__global__ void __cluster_dims__(2, 1, 1) __launch_bounds__(384, 1)
fused_kernel(const __grid_constant__ Params P) {
    extern __shared__ __align__(1024) uint8_t smem_raw[];
    const uint32_t sb = (uint32_t)__cvta_generic_to_shared(smem_raw);
    const int tid = threadIdx.x, warp = tid >> 5, lane = tid & 31;
    const int k0 = blockIdx.x >> 1, i7 = ((k0 - 36) * 37) >> 8;
    const int G = k0 < 4 ? 0 : k0 < 36 ? (k0 - 4) & 7 : k0 - 35 - 7 * i7, gi = k0 < 4 ? k0 : k0 < 36 ? (k0 - 4) >> 3 : i7;
    unsigned role = 16 * (G >> 1) + (k0 >= 4 && k0 < 36 ? 0 : 8) + 4 * (gi >> 1) + 2 * (G & 1) + (gi & 1);
    asm volatile("" : "+r"(role));
    const int m = (role >> 2) & 15, c = role & 3, r = blockIdx.x & 1, j = 2 * c + r, cc = c >> 1;
    const uint32_t bar = sb + OFF_BAR;

    if (warp >= 8) {
        asm volatile("setmaxnreg.dec.sync.aligned.u32 24;");
        if (warp == 8) {
            const bool el = elect_one();
            if (el) {
                #pragma unroll
                for (int i = 4; i < B_NUM; i++) mbar_init(bar + i * 8, i == B_MISC ? 3 : i < B_EMPTY ? 1 : i < B_XFREE ? 8 : i < B_KVRDY ? 4 : 2);
                #pragma unroll
                for (int i = B_RXA; i < B_RXFREE; i++) mbar_expect_tx(bar + i * 8, i < B_RXB ? 16384 : i < B_RXC ? 6144 : 8192);
                asm volatile("fence.mbarrier_init.release.cluster;" ::: "memory");
            }
            __syncwarp();
            bar_arrive(0, 384);
            asm volatile("barrier.cluster.arrive.relaxed.aligned;" ::: "memory");
            if (el) {
                #pragma unroll 1
                for (int s = 0; s < 4; s++) {
                    if (s == 1) {
                        #pragma unroll 1
                        for (int i = 0; i < 4; i++) {
                            mbar_expect_tx(bar + (B_XFULL + 4 + i) * 8, STB);
                            tma3d(sb + OFF_INC + i * STB, &P.x, 0, m * 128 + 64, 2 * i, bar + (B_XFULL + 4 + i) * 8);
                        }
                    }
                    mbar_expect_tx(bar + (B_FULL + s) * 8, STB);
                    tma3d(sb + s * STB, &P.kv, 64 * j, 64 * s, 1, bar + (B_FULL + s) * 8);
                }
                mbar_wait(bar + B_XFREE * 8, 0);
                #pragma unroll 1
                for (int s = 4; s < 8; s++) {
                    mbar_expect_tx(bar + (B_FULL + s) * 8, STB);
                    tma3d(sb + s * STB, &P.kv, 64 * j, 64 * s, 1, bar + (B_FULL + s) * 8);
                }
                if (m < 8) pf3d(&P.w1a, 176 * j, 64 * m, 0);
                else { pf3d(&P.q, 64 * j, 64 * (m - 8), 0); pf3d(&P.w1b, 176 * j + 128, 64 * (m - 8), 0); }
                mbar_wait(bar + (B_FULL + 7) * 8, 0);
                #pragma unroll 1
                for (int n = -1; n < 7; n++) {
                    const uint32_t fb = bar + (B_FULL + (n < 0 ? 8 : n)) * 8;
                    if (n >= 0) mbar_wait(bar + (B_EMPTY + n) * 8, 0);
                    mbar_expect_tx(fb, STB);
                    tma3d(n < 0 ? sb + OFF_SPARE : sb + n * STB, &P.w1a, 176 * j, 64 * (n & 7), 0, fb);
                }
                {
                    const int s = m & 7, jj = j ^ ((s >> 1) & 1), ch = 4 * r + 2 * (m >> 3);
                    if (s == 5 || s == 7) pf3d(&P.wo, 0, 64 * jj, ch);
                    else pf3d(&P.w2, 0, 176 * jj + (s < 4 ? 64 * (s & 1) : 128), ch);
                }
                #pragma unroll 1
                for (int n = -1; n < 7; n++) {
                    const int s = n & 7;
                    const uint32_t fb = bar + (B_FULL + (n < 0 ? 9 : n)) * 8;
                    mbar_wait(bar + (B_EMPTY + s) * 8, n >= 0);
                    mbar_expect_tx(fb, STB);
                    tma3d(sb + s * STB, &P.q, 64 * j, 64 * s, 0, fb);
                    tma3d(sb + s * STB + 8192, &P.w1b, 176 * j + 128, 64 * s, 0, fb);
                }
                #pragma unroll 1
                for (int g = 0; g < 2; g++) {
                    mbar_wait(bar + (B_HAST + g) * 8, 0);
                    mbar_wait(bar + (B_RXFREE + g) * 8, 0);
                    asm volatile("cp.async.bulk.shared::cluster.shared::cta.mbarrier::complete_tx::bytes [%0], [%1], 16384, [%2];"
                        :: "r"(mapa(sb + OFF_INC + g * 32768, r ^ 1)), "r"(sb + OFF_INC + g * 32768 + 16384), "r"(mapa(bar + (B_RXA + g) * 8, r ^ 1)) : "memory");
                    if (g == 0) {
                        mbar_wait(bar + (B_EMPTY + 7) * 8, 1);
                        mbar_expect_tx(bar + (B_FULL + 10) * 8, STB);
                        tma3d(sb + OFF_SPARE, &P.wo, 0, 64 * (j ^ 1), 4 * r + 2 * (cc ^ 1), bar + (B_FULL + 10) * 8);
                    }
                }
                #pragma unroll 1
                for (int s = 0; s < 8; s += 2) {
                    const int jj = j ^ ((s >> 1) & 1), ch = 4 * r + 2 * (cc ^ 1);
                    const uint32_t fb = bar + (B_FULL + s) * 8;
                    mbar_wait(bar + (B_EMPTY + s) * 8, 0);
                    mbar_expect_tx(fb, STB);
                    tma3d(sb + s * STB, &P.w2, 0, 176 * jj + 32 * (s & 4), ch, fb);
                    mbar_wait(bar + (B_EMPTY + s + 1) * 8, 0);
                    if (s < 6) {
                        mbar_expect_tx(fb + 8, STB);
                        tma3d(sb + (s + 1) * STB, s < 4 ? &P.w2 : &P.wo, 0, s < 4 ? 176 * jj + 64 : 64 * jj, ch, fb + 8);
                    }
                }
                mbar_expect_tx(bar + B_XRES * 8, STB);
                tma3d(sb + 7 * STB, &P.xr, 0, m * 128, 4 * r + c, bar + B_XRES * 8);
                #pragma unroll 1
                for (int q = 0; q < 4; q++) {
                    const int jj = j ^ (q & 1), ch = 4 * r + (c ^ (q >> 1) ^ 1);
                    const uint32_t dst = q ? sb + (2 * q - 2) * STB : sb + OFF_INC, fb = bar + (B_FULLB + q) * 8;
                    if (q) mbar_wait(bar + (B_EMPTY + 2 * q - 2) * 8, 1); else mbar_wait(bar + B_PBDONE * 8, 0);
                    mbar_expect_tx(fb, 30720);
                    tma3d(dst, &P.w2h, 0, 176 * jj, ch, fb);
                    if (q) mbar_wait(bar + (B_EMPTY + 2 * q - 1) * 8, 1);
                    tma3d(dst + 11264, &P.w2h, 0, 176 * jj + 88, ch, fb);
                    tma3d(dst + 22528, &P.woh, 0, 64 * jj, ch, fb);
                }
            }
        } else if (warp == 11) {
            asm volatile("barrier.cluster.arrive.relaxed.aligned;" ::: "memory");
            if (lane == 0) asm volatile("prefetch.tensormap [%0];" :: "l"(&P.kv) : "memory");
            bar_sync(0, 384);
            if (lane < 8) {
                const CUtensorMap* tm = &P.q + lane;
                asm volatile("prefetch.tensormap [%0];" :: "l"(tm) : "memory");
            }
            if ((sb & 0x3FFFF) != SMEM_BASE) __trap();
            sts128(sb + OFF_ONES + lane * 16, ONES2, ONES2, ONES2, ONES2);
            sts128(sb + OFF_ONES + 512 + lane * 16, ONES2, ONES2, ONES2, ONES2);
            uint32_t bv[3];
            #pragma unroll
            for (int u = 0; u < 3; u++) bv[u] = (lane + 32 * u < 88 && 88 * j + lane + 32 * u < 688) ? __ldg((const uint32_t*)P.b1 + 88 * j + lane + 32 * u) : 0u;
            const uint32_t b2v = __ldg((const uint32_t*)(P.b2 + 256 * r + 64 * c) + lane);
            #pragma unroll
            for (int u = 0; u < 3; u++) {
                const int idx = lane + 32 * u;
                if (idx < 88) sts32(sb + OFF_B1 + (idx & 3) * 96 + (idx >> 2) * 4, mul2(bv[u], 0x3F003F00u));
            }
            sts32(sb + OFF_B2 + (lane & 3) * 32 + (lane >> 2) * 4, b2v);
            fence_async_smem();
            __syncwarp();
            if (lane == 0) {
                mbar_arrive(bar + B_MISC * 8);
            }
            if (lane == 0) {
                unsigned long long t0, t1;
                asm volatile("mov.u64 %0, %globaltimer;" : "=l"(t0));
                while (true) {
                    uint32_t ok;
                    asm volatile("{ .reg .pred p; mbarrier.try_wait.parity.shared::cta.b64 p, [%1], 0, 1000000; selp.u32 %0, 1, 0, p; }" : "=r"(ok) : "r"(bar + B_DONE * 8) : "memory");
                    if (ok) break;
                    asm volatile("mov.u64 %0, %globaltimer;" : "=l"(t1));
                    if (t1 - t0 > 2000000000ull) __trap();
                }
            }
        } else {
            const int g = warp - 9;
            asm volatile("barrier.cluster.arrive.relaxed.aligned;" ::: "memory");
            bar_sync(0, 384);
            unsigned ep;
            asm volatile("ld.relaxed.gpu.global.u32 %0, [%1];" : "=r"(ep) : "l"(&g_epoch) : "memory");
            {
                uint32_t v[8];
                #pragma unroll
                for (int u = 0; u < 8; u++) asm volatile("ld.global.nc.u32 %0, [%1];" : "=r"(v[u]) : "l"((const uint32_t*)P.wphi + j * 512 + g * 256 + u * 32 + lane) : "memory");
                #pragma unroll
                for (int u = 0; u < 8; u++) {
                    const int row = u * 4 + (lane >> 3);
                    const uint32_t wv = pack2(bflo(v[u]) * 1.4426950408889634f, bfhi(v[u]) * 1.4426950408889634f);
                    const uint32_t lo = g ? 0u : wv, hi = g ? wv : 0u;
                    sts128(sb + OFF_WBIG + g * 4096 + row * 128 + (((lane ^ row) & 7) << 4), u < 4 ? lo : 0u, u < 4 ? 0u : lo, u < 4 ? hi : 0u, u < 4 ? 0u : hi);
                }
                fence_async_smem();
                __syncwarp();
                if (lane == 0) mbar_arrive(bar + B_MISC * 8);
            }
            const float* kvg = g_kv[ep & 1][j];
            unsigned* cnt = &g_cnt[ep & 1][j][0];
            {
                float4* z = (float4*)&g_kv[(ep + 1) & 1][j][m * 136];
                if (lane < 18 - 2 * g) z[g * 18 + lane] = make_float4(0.f, 0.f, 0.f, 0.f);
                if (m == 0 && lane < 8) g_cnt[(ep + 1) & 1][j][lane] = 0;
            }
            asm volatile("barrier.cluster.wait.acquire.aligned;" ::: "memory");
            if (lane == 0) {
                sts32(sb + OFF_EP, ep);
                mbar_wait(bar + (B_KVST + g) * 8, 0);
                asm volatile("cp.reduce.async.bulk.global.shared::cta.bulk_group.add.f32 [%0], [%1], 8192;"
                    :: "l"(kvg), "r"(sb + OFF_INC + g * 32768 + R_KVP) : "memory");
                asm volatile("cp.reduce.async.bulk.global.shared::cta.bulk_group.add.f32 [%0], [%1], 512;"
                    :: "l"(kvg + 2048), "r"(sb + OFF_KVB + g * 512) : "memory");
                asm volatile("cp.async.bulk.commit_group;" ::: "memory");
                asm volatile("cp.async.bulk.wait_group.read 0;" ::: "memory");
                mbar_arrive(bar + (B_KVRD + g) * 8);
                asm volatile("mbarrier.arrive.relaxed.cluster.shared::cluster.b64 _, [%0];" :: "r"(mapa(bar + (B_RXFREE + g) * 8, r ^ 1)) : "memory");
                asm volatile("cp.async.bulk.wait_group 0;" ::: "memory");
                asm volatile("red.relaxed.gpu.global.add.u32 [%0], 1;" :: "l"(cnt) : "memory");
                if (g == 1) {
                    unsigned v;
                    do { asm volatile("ld.relaxed.gpu.global.u32 %0, [%1];" : "=r"(v) : "l"(cnt) : "memory"); } while (v < 32);
                    asm volatile("fence.proxy.async.global;" ::: "memory");
                    mbar_expect_tx(bar + B_KVRAW * 8, KV_FLOATS * 4);
                    asm volatile("cp.async.bulk.shared::cluster.global.mbarrier::complete_tx::bytes [%0], [%1], %2, [%3];"
                        :: "r"(sb + OFF_KVB), "l"(kvg), "r"(KV_FLOATS * 4), "r"(bar + B_KVRAW * 8) : "memory");
                }
            }
            __syncwarp();
            mbar_wait(bar + B_KVRAW * 8, 0);
            {
                uint32_t kb = sb + OFF_KVB + g * 4096 + lane * 16, zs = sb + OFF_KVB + 8192 + g * 256 + lane * 4;
                #pragma unroll 1
                for (int h = 0; h < 2; h++, kb += 2048, zs += 128) {
                    uint32_t w[8];
                    #pragma unroll
                    for (int u = 0; u < 4; u += 2) {
                        uint32_t v[4], y[4];
                        lds128(v, kb + u * 512); lds128(y, kb + u * 512 + 512);
                        w[2 * u] = pack2v(__uint_as_float(v[0]), __uint_as_float(v[1])); w[2 * u + 1] = pack2v(__uint_as_float(v[2]), __uint_as_float(v[3]));
                        w[2 * u + 2] = pack2v(__uint_as_float(y[0]), __uint_as_float(y[1])); w[2 * u + 3] = pack2v(__uint_as_float(y[2]), __uint_as_float(y[3]));
                    }
                    const float z = __uint_as_float(lds32(zs));
                    __syncwarp();
                    stsm4(kb, w[0], w[1], w[2], w[3]);
                    stsm4(kb + 768, w[4], w[5], w[6], w[7]);
                    const uint32_t zw = pack2(z, z);
                    sts128(kb + 512 + (lane >> 4) * 512, zw, zw, zw, zw);
                }
            }
            fence_async_smem();
            __syncwarp();
            if (lane == 0) mbar_arrive(bar + B_KVRDY * 8);
            const uint32_t* fp = (const uint32_t*)&g_flag[m * 8 + j][g * 3] + (lane < 12 ? lane : 0);
            const uint32_t xb = sb + (g ? OFF_INC + 40960 : OFF_WBIG);
            int state = 1;
            while (true) {
                uint32_t f;
                asm volatile("ld.relaxed.gpu.global.u32 %0, [%1];" : "=r"(f) : "l"(fp) : "memory");
                const uint32_t missing = __ballot_sync(0xffffffffu, f != ep + 1);
                #pragma unroll 1
                for (int late = 1; late >= 0; late--) {
                    if ((missing & (late ? 0xF : 0xFF0)) || (state & (2 << late))) continue;
                    state |= 2 << late;
                    if (!late) { const unsigned t0 = clock(); while ((unsigned)clock() - t0 < 200) {} }
                    mbar_wait(bar + B_PBDONE * 8, 0);
                    mbar_wait(bar + (B_EMPTY + ((late | g) ? 6 : 0)) * 8, 1);
                    if (elect_one()) {
                        const uint32_t bytes = late ? 8192 : 16384, tbar = bar + (B_TILE + 2 * late + g) * 8;
                        mbar_expect_tx(tbar, bytes);
                        asm volatile("cp.async.bulk.shared::cluster.global.mbarrier::complete_tx::bytes [%0], [%1], %2, [%3];"
                            :: "r"(late ? sb + 6 * STB + g * 65536 : xb), "l"(g_part + (size_t)((m * 8 + j) * 8 + g * 3 + 1 - late) * 512), "r"(bytes), "r"(tbar) : "memory");
                    }
                    __syncwarp();
                }
                if (state == 7) break;
                mbar_wait(bar + B_PBDONE * 8, 0);
            }
        }
    } else {
        const bool el0 = elect_one();
        if (warp == 1 || warp == 2) asm volatile("prefetch.global.L2 [%0];" :: "l"(P.xp + (m * 128 + 8 * j) * 512 + (tid - 32) * 64) : "memory");
        if (el0 && warp == 0) {
            #pragma unroll
            for (int i = 0; i < 4; i++) mbar_init(bar + (B_XFULL + i) * 8, 1);
            asm volatile("fence.mbarrier_init.release.cluster;" ::: "memory");
            #pragma unroll
            for (int i = 0; i < 4; i++) {
                mbar_expect_tx(bar + (B_XFULL + i) * 8, STB);
                tma3d(sb + (4 + i) * STB, &P.x, 0, m * 128, 2 * i, bar + (B_XFULL + i) * 8);
            }
        }
        __syncwarp();
        asm volatile("barrier.cluster.arrive.relaxed.aligned;" ::: "memory");
        asm volatile("setmaxnreg.inc.sync.aligned.u32 240;");
        bar_sync(0, 384);
        const int wg = __shfl_sync(0xffffffffu, warp >> 2, 0), w = warp & 3, t = lane & 3, g = lane >> 2, tw = tid & 127;
        const uint32_t reg = sb + OFF_INC + wg * 32768;
        const int lrow = 16 * w + (lane & 15);
        const uint32_t swz = ((lane >> 4) ^ (lane & 7)) << 4;
        const uint32_t phia = reg + (t >> 1) * 8192 + (16 * w + g) * 128 + (((4 * (t & 1)) ^ (t & 2) ^ g) << 4);
        constexpr uint64_t dB = (uint64_t)(SMEM_BASE >> 4) | desc_hi(8192, 1024, 1);

        uint32_t A[32][4];
        {
            const uint32_t xst = sb + (wg ? OFF_INC : 4 * STB) + lrow * 128;
            #define LOADX(b, i) do { mbar_wait(bar + (B_XFULL + (b) + (i)) * 8, 0); \
                _Pragma("unroll") for (int k = 8 * (i); k < 8 * (i) + 8; k++) ldsm4(A[k], xst + (k >> 2) * 8192 + (swz ^ (32 * (k & 3)))); } while (0)
            uint32_t sc0, sc1, of0, of1;
            float base0 = 0.f, base1 = 0.f;
            bool centred = false;
            while (true) {
                float st[4];
                if (wg == 0) {
                    float s4[4][4], q4[4];
                    #pragma unroll
                    for (int i = 0; i < 4; i++) { s4[0][i] = 0.f; s4[1][i] = 0.f; s4[2][i] = 0.f; s4[3][i] = 0.f; q4[i] = 0.f; }
                    LOADX(0, 0);
                    #pragma unroll
                    for (int i = 0; i < 4; i++) {
                        if (i < 3) LOADX(0, i + 1);
                        uint32_t c[4];
                        #pragma unroll
                        for (int k = 8 * i; k < 8 * i + 8; k++) {
                            mma_ones(s4[k & 3], A[k]);
                            #pragma unroll
                            for (int e = 0; e < 4; e++) c[e] = (k & 7) ? fma2(A[k][e], A[k][e], c[e]) : mul2(A[k][e], A[k][e]);
                        }
                        mma_ones(q4, c);
                    }
                    st[0] = (s4[0][0] + s4[1][0]) + (s4[2][0] + s4[3][0]); st[1] = (s4[0][2] + s4[1][2]) + (s4[2][2] + s4[3][2]); st[2] = q4[0]; st[3] = q4[2];
                } else {
                    uint32_t ps[4][4];
                    LOADX(4, 0); LOADX(4, 1); LOADX(4, 2); LOADX(4, 3);
                    #pragma unroll
                    for (int i = 0; i < 4; i++) stats8(A + 8 * i, ps[i]);
                    #pragma unroll
                    for (int i = 0; i < 4; i++) {
                        const uint32_t y = add2(ps[0][i], ps[1][i]), z = add2(ps[2][i], ps[3][i]);
                        st[i] = (bflo(y) + bfhi(y)) + (bflo(z) + bfhi(z));
                    }
                    #pragma unroll
                    for (int o = 1; o <= 2; o <<= 1) {
                        #pragma unroll
                        for (int i = 0; i < 4; i++) st[i] += __shfl_xor_sync(0xffffffffu, st[i], o);
                    }
                }
                const float mean0 = st[0] * (1.f / 512.f), mean1 = st[1] * (1.f / 512.f), q0 = st[2] * (1.f / 512.f), q1 = st[3] * (1.f / 512.f);
                const float var0 = fmaf(-mean0, mean0, q0), var1 = fmaf(-mean1, mean1, q1);
                const float rs0 = rsq(fmaxf(var0, 0.f) + 1e-5f), rs1 = rsq(fmaxf(var1, 0.f) + 1e-5f);
                const uint32_t mb = pack2(base0 + mean0, base1 + mean1);
                sc0 = pack2(rs0, rs0); sc1 = pack2(rs1, rs1);
                const float d0 = (base0 - bflo(mb)) * bflo(sc0), d1 = (base1 - bfhi(mb)) * bflo(sc1);
                of0 = pack2(d0, d0); of1 = pack2(d1, d1);
                if (centred || !__any_sync(0xffffffffu, !(var0 >= 0.5f * q0) || !(var1 >= 0.5f * q1))) break;
                base0 = bflo(mb); base1 = bfhi(mb);
                const uint32_t m0 = pack2(base0, base0), m1 = pack2(base1, base1);
                #pragma unroll 1
                for (int k = 0; k < 32; k++) {
                    const uint32_t a = xst + (k >> 2) * 8192 + (swz ^ (32 * (k & 3)));
                    uint32_t v[4];
                    ldsm4(v, a);
                    stsm4(a, sub2(v[0], m0), sub2(v[1], m1), sub2(v[2], m0), sub2(v[3], m1));
                }
                fence_async_smem();
                __syncwarp();
                centred = true;
            }
            if (lane == 0) mbar_arrive(bar + (B_XFREE + wg) * 8);
            norm4(A, sc0, sc1, of0, of1);
            if (wg == 1) bar_sync(6, 256);
            float acc[64];
            #pragma unroll
            for (int s = 0; s < 8; s++) {
                MMA_STAGE(0, true, if (s == 0 && k == 0) wgmma_rs128_first(acc, A[0], d); else wgmma_rs128(acc, A[4 * s + k], d));
                if (s < 7) norm4(A + 4 * s + 4, sc0, sc1, of0, of1);
                STAGE_END(true);
            }
            mbar_wait(bar + B_MISC * 8, 0);
            wg_wait<0>();
            release(sb, 7, lane);

            float p[32];
            uint32_t ka[4][4];
            logits_issue(acc, ka, p);
            mbar_wait(bar + (B_XFREE + 1) * 8, 0);
            {
                const uint32_t va = reg + R_V + lrow * 64 + (((lane >> 4) ^ ((lane >> 1) & 3)) << 4);
                #pragma unroll
                for (int h = 0; h < 4; h++) {
                    const float* v = acc + 32 + 8 * h;
                    stsm4((va ^ (32 * (h & 1))) + (h >> 1) * 4096, pack2v(v[0], v[1]), pack2v(v[2], v[3]), pack2v(v[4], v[5]), pack2v(v[6], v[7]));
                }
            }
            wg_wait<0>();
            features(p, phia);
            fence_async_smem();
            bar_sync(1 + wg, 128);
            float kv0[20], kv1[20];
            wg_fence();
            kv_mma(kv0, kv1, wg);
            const uint32_t kvo = reg + R_KVP + lane * 16, zo = sb + OFF_KVB + wg * 512 + (w * 16 + g) * 4;
            wg_wait<1>();
            store_kv(kv0, kvo + w * 1024, zo, w >> 1, t);
            wg_wait<0>();
            store_kv(kv1, kvo + 4096 + (w ^ 1) * 1024, (zo ^ 64) + 256, w >> 1, t);
            fence_async_smem();
            __syncwarp();
            if (lane == 0) mbar_arrive(bar + (B_KVST + wg) * 8);
        }
        const uint32_t rreg = mapa(reg + tw * 16, r ^ 1);
        uint32_t Ha[8][4];
        {
            float acc[64];
            bar_sync(5 + wg, 256);
            #pragma unroll
            for (int s = 0; s < 8; s++) {
                MMA_STAGE(1, true, if (s == 0 && k == 0) wgmma_rs128_first(acc, A[0], d); else wgmma_rs128(acc, A[4 * s + k], d));
                STAGE_END(true);
            }
            mbar_wait(bar + (B_KVRD + wg) * 8, 0);
            uint32_t bw[4][4];
            #pragma unroll
            for (int i = 0; i < 4; i++) lds128(bw[i], sb + OFF_B1 + t * 96 + i * 16);
            wg_wait<0>();
            release(sb, 7, lane);
            #pragma unroll
            for (int i = 7; i >= 0; i--) {
                pre_gelu(Ha[i], acc + 8 * i, bw[i >> 1][2 * (i & 1)], bw[i >> 1][2 * (i & 1) + 1]);
                gelu4(Ha[i]);
                sts128(reg + tw * 16 + (8 + i) * 2048, Ha[i][0], Ha[i][1], Ha[i][2], Ha[i][3]);
            }
            fence_async_smem();
            __syncwarp();
            if (lane == 0) mbar_arrive(bar + (B_HAST + wg) * 8);
        }
        uint32_t Hb[7][4];
        uint32_t Pa[8][4], Pb[7][4];
        {
            float acc[56];
            bar_sync(5 + wg, 256);
            #pragma unroll
            for (int s = 0; s < 8; s++) {
                MMA_STAGE(2, true, if (s == 0 && k == 0) wgmma_rs112_first(acc, A[0], d); else wgmma_rs112(acc, A[4 * s + k], d));
                if (s >= 2 && s < 6) { lds128(Ha[2 * s - 4], reg + tw * 16 + (2 * s + 4) * 2048); lds128(Ha[2 * s - 3], reg + tw * 16 + (2 * s + 5) * 2048); }
                if (s == 6) mbar_wait(bar + (B_RXA + wg) * 8, 0);
                if (s >= 6) {
                    #pragma unroll
                    for (int i = 4 * s - 24; i < 4 * s - 20; i++) lds128(Pa[i], reg + i * 2048 + tw * 16);
                }
                STAGE_END(true);
            }
            wg_wait<0>();
            release(sb, 7, lane);
            float p[32];
            uint32_t qa[4][4];
            logits_issue(acc, qa, p);
            bar_sync(1 + wg, 128);
            if (tw == 0) asm volatile("mbarrier.arrive.relaxed.cluster.shared::cluster.b64 _, [%0];" :: "r"(mapa(bar + (B_RXFREE2 + wg) * 8, r ^ 1)) : "memory");
            uint32_t bw[2][4];
            lds128(bw[0], sb + OFF_B1 + t * 96 + 64); lds128(bw[1], sb + OFF_B1 + t * 96 + 80);
            #pragma unroll
            for (int i = 0; i < 3; i++) pre_gelu(Hb[i], acc + 32 + 8 * i, bw[i >> 1][2 * (i & 1)], bw[i >> 1][2 * (i & 1) + 1]);
            if (wg < 2) { gelu4(Hb[0]); gelu4(Hb[1]); gelu4(Hb[2]); }
            wg_wait<0>();
            features(p, phia);
            fence_async_smem();
            if (wg >= 1) {
                mbar_wait(bar + (B_RXFREE2 + wg) * 8, 0);
                const uint32_t rbar = mapa(bar + (B_RXB + wg) * 8, r ^ 1);
                #pragma unroll
                for (int i = 0; i < 3; i++) st_async4(rreg + (8 + i) * 2048, Hb[i], rbar);
            }
            mbar_wait(bar + B_KVRDY * 8, 0);
        }
        const unsigned ep = lds32(sb + OFF_EP);
        const uint32_t tag = (ep + 1) & 1;
        #define PART(o) (g_part + (size_t)((m * 8 + 2 * (o) + r) * 8 + wg * 3 + (c ^ (o)) - 1) * 512 + tw)
        #define FLAG(o) (&g_flag[m * 8 + 2 * (o) + r][wg * 3 + (c ^ (o)) - 1])
        const uint32_t xb = sb + (wg ? OFF_INC + 40960 : OFF_WBIG) + tw * 16;
        float own[32];
        {
            float o[4][12], acc[64];
            bar_sync(5 + wg, 256);
            wg_fence();
            readout_mma(o, wg);
            wg_commit();
            #pragma unroll
            for (int s = 0; s < 8; s++) {
                MMA_STAGE(3, false, if (s == 0 && k == 0) wgmma_rs128_first(acc, Ha[0], d); else if (G2_HAS(s, k)) wgmma_rs128(acc, G2_A(s, k), d));
                if (s == 0 && wg < 1) {
                    mbar_wait(bar + (B_RXFREE2 + wg) * 8, 0);
                    const uint32_t rbar = mapa(bar + (B_RXB + wg) * 8, r ^ 1);
                    #pragma unroll
                    for (int i = 0; i < 3; i++) st_async4(rreg + (8 + i) * 2048, Hb[i], rbar);
                }
                if (s == 1) {
                    wg_wait<2>();
                    const uint32_t rbar = mapa(bar + (B_RXC + wg) * 8, r ^ 1);
                    #pragma unroll
                    for (int h = 0; h < 4; h++) {
                        const float r0 = rcp(o[h][8] + 1e-6f), r1 = rcp(o[h][10] + 1e-6f);
                        Hb[3 + h][0] = pack2(o[h][0] * r0, o[h][1] * r0); Hb[3 + h][1] = pack2(o[h][2] * r1, o[h][3] * r1);
                        Hb[3 + h][2] = pack2(o[h][4] * r0, o[h][5] * r0); Hb[3 + h][3] = pack2(o[h][6] * r1, o[h][7] * r1);
                        st_async4(rreg + (11 + h) * 2048, Hb[3 + h], rbar);
                    }
                }
                if (s == 4) {
                    mbar_wait(bar + (B_RXB + wg) * 8, 0);
                    #pragma unroll
                    for (int i = 0; i < 3; i++) lds128(Pb[i], reg + (8 + i) * 2048 + tw * 16);
                }
                if (s == 5) {
                    mbar_wait(bar + (B_RXC + wg) * 8, 0);
                    #pragma unroll
                    for (int i = 3; i < 7; i++) lds128(Pb[i], reg + (8 + i) * 2048 + tw * 16);
                }
                if (s == 7 && wg == 0 && lane == 0) mbar_arrive(bar + B_PBDONE * 8);
                STAGE_END(false);
            }
            wg_wait<0>();
            release(sb, 7, lane);
            uint32_t pk[8][4];
            pack_tile(pk, acc, tag);
            mbar_wait(bar + (B_EMPTY + 2) * 8, 1);
            #pragma unroll
            for (int i = 0; i < 8; i++) {
                const int oc = 2 * (cc ^ 1) + (i >> 2);
                stg128(PART(oc) + (i & 3) * 128, pk[i]);
                if ((i & 3) == 3) set_flag(FLAG(oc), w, ep + 1, lane);
            }
        }
        const uint32_t tb = sb + 6 * STB + wg * 65536;
        const uint4* const mine = g_part + (size_t)((m * 8 + j) * 8 + wg * 3) * 512 + tw;
        uint32_t xv[4][4];
        #pragma unroll
        for (int hf = 0; hf < 2; hf++) {
            float oth[32];
            mbar_wait(bar + (B_FULLB + 2 * hf) * 8, 0);
            bar_sync(5 + wg, 256);
            #pragma unroll
            for (int n = 0; n < 8; n++) {
                const int s = (n & 1) | ((n & 2) << 1) | ((n & 4) >> 1);
                if (n == 4) mbar_wait(bar + (B_FULLB + 2 * hf + 1) * 8, 0);
                if (n == 0 || n == 4) wg_fence();
                #pragma unroll
                for (int k = 0; k < 4; k++) {
                    const int q = 2 * hf + ((s >> 1) & 1);
                    const uint64_t d = dB + (((q ? (2 * q - 2) * STB : OFF_INC) + (s < 4 ? (s & 1) * 8192 : (s & 1) ? 22528 : 16384) + k * 2048) >> 4);
                    if (hf == 0) { if (s == 0 && k == 0) wgmma_rs64_first(oth, Ha[0], d); else if (G2_HAS(s, k)) wgmma_rs64(oth, G2_A(s, k), d); }
                    else { if (s == 0 && k == 0) wgmma_rs64_first(own, Ha[0], d); else if (G2_HAS(s, k)) wgmma_rs64(own, G2_A(s, k), d); }
                }
                if (s == 7 && (hf & wg) == 0) bar_arrive(6 - wg, 256);
                if (s == 7) wg_commit();
            }
            if (hf == 0) {
                wg_wait<0>();
                uint32_t pk[4][4];
                pack_tile(pk, oth, tag);
                #pragma unroll
                for (int i = 0; i < 4; i++) stg128(PART(c ^ 1) + i * 128, pk[i]);
                set_flag(FLAG(c ^ 1), w, ep + 1, lane);
                mbar_wait(bar + B_XRES * 8, 0);
                uint32_t bw[2][4];
                lds128(bw[0], sb + OFF_B2 + t * 32); lds128(bw[1], sb + OFF_B2 + t * 32 + 16);
                #pragma unroll
                for (int i = 0; i < 4; i++) ldsm4(xv[i], sb + 7 * STB + wg * 8192 + lrow * 128 + (swz ^ (32 * i)));
                if (wg < 2) {
                    #pragma unroll
                    for (int i = 0; i < 16; i++) xv[i >> 2][i & 3] = add2(xv[i >> 2][i & 3], bw[i >> 3][(i >> 1) & 3]);
                }
            }
        }
        {
            uint32_t ost = tb + 8192 + wg * 16384 + w * 2048, oa = ost + (lane & 15) * 128 + swz;
            uint32_t u[8][4];
            mbar_wait(bar + (B_TILE + wg) * 8, 0);
            #pragma unroll
            for (int i = 0; i < 8; i++) lds128(u[i], xb + i * 2048);
            check_tile(u, mine + 512, tag);
            wg_wait<0>();
            if (wg < 2) {
                #pragma unroll
                for (int i = 0; i < 16; i++)
                    xv[i >> 2][i & 3] = add2(xv[i >> 2][i & 3], add2(add2(u[i >> 2][i & 3], u[4 + (i >> 2)][i & 3]), pack2(own[2 * i], own[2 * i + 1])));
            }
            uint32_t v[4][4];
            mbar_wait(bar + (B_TILE + 2 + wg) * 8, 0);
            #pragma unroll
            for (int i = 0; i < 4; i++) lds128(v[i], tb + tw * 16 + i * 2048);
            check_tile(v, mine, tag);
            if (lane == 0) mbar_arrive(bar + B_DONE * 8);
            #pragma unroll
            for (int i = 0; i < 4; i++) {
                stsm4(oa ^ (32 * i), add2(xv[i][0], v[i][0]), add2(xv[i][1], v[i][1]), add2(xv[i][2], v[i][2]), add2(xv[i][3], v[i][3]));
            }
            __syncwarp();
            uint4* op = (uint4*)P.outp + (size_t)(m * 128 + wg * 64 + 16 * w + (lane >> 3)) * 64 + (4 * r + c) * 8 + (lane & 7);
            #pragma unroll
            for (int i = 0; i < 4; i++) lds128(v[i], ((ost + (lane >> 3) * 128 + (((lane ^ (lane >> 3)) & 7) << 4)) ^ ((i & 1) * 64)) + i * 512);
            #pragma unroll
            for (int i = 0; i < 4; i++) op[i * 256] = make_uint4(v[i][0], v[i][1], v[i][2], v[i][3]);
            if (blockIdx.x == 0 && tid == 128) asm volatile("st.relaxed.gpu.global.u32 [%0], %1;" :: "l"(&g_epoch), "r"(ep + 1) : "memory");
        }
    }
}

typedef CUresult (*EncFn)(CUtensorMap*, CUtensorMapDataType, cuuint32_t, void*, const cuuint64_t*, const cuuint64_t*, const cuuint32_t*,
                          const cuuint32_t*, CUtensorMapInterleave, CUtensorMapSwizzle, CUtensorMapL2promotion, CUtensorMapFloatOOBfill);

void encode(EncFn enc, CUtensorMap* tm, const void* base, int rank, cuuint64_t d0, cuuint64_t d1, cuuint64_t d2, cuuint64_t s1, cuuint64_t s2,
            cuuint32_t b0, cuuint32_t b1, cuuint32_t b2) {
    cuuint64_t gd[3] = {d0, d1, d2}, gs[2] = {s1, s2};
    cuuint32_t bd[3] = {b0, b1, b2}, es[3] = {1, 1, 1};
    enc(tm, CU_TENSOR_MAP_DATA_TYPE_BFLOAT16, rank, const_cast<void*>(base), gd, gs, bd, es, CU_TENSOR_MAP_INTERLEAVE_NONE,
        CU_TENSOR_MAP_SWIZZLE_128B, CU_TENSOR_MAP_L2_PROMOTION_L2_128B, CU_TENSOR_MAP_FLOAT_OOB_FILL_NONE);
}

}

extern "C" void kernel_launch(void* const* d_in, const int* in_sizes, int n_in, void* d_out, int out_size) {
    (void)in_sizes; (void)n_in; (void)out_size;
    static EncFn enc = nullptr;
    if (!enc) {
        void* fn = nullptr;
        cudaDriverEntryPointQueryResult qr;
        cudaGetDriverEntryPoint("cuTensorMapEncodeTiled", &fn, cudaEnableDefault, &qr);
        enc = (EncFn)fn;
        cudaFuncSetAttribute(fused_kernel, cudaFuncAttributeMaxDynamicSharedMemorySize, SMEM_BYTES);
    }
    Params P;
    encode(enc, &P.x, d_in[0], 3, 64, 2048, 8, 1024, 128, 64, 64, 2);
    encode(enc, &P.kv, d_in[1], 3, 512, 512, 3, 3072, 1024, 64, 64, 2);
    encode(enc, &P.q, d_in[1], 3, 512, 512, 3, 3072, 1024, 64, 64, 1);
    encode(enc, &P.w1a, d_in[5], 3, 1376, 512, 2, 2752, 128, 64, 64, 2);
    encode(enc, &P.w1b, d_in[5], 3, 1376, 512, 2, 2752, 128, 64, 64, 1);
    encode(enc, &P.w2h, d_in[7], 3, 64, 1376, 8, 1024, 128, 64, 88, 1);
    encode(enc, &P.woh, d_in[3], 3, 64, 512, 8, 1024, 128, 64, 64, 1);
    encode(enc, &P.w2, d_in[7], 3, 64, 1376, 8, 1024, 128, 64, 64, 2);
    encode(enc, &P.wo, d_in[3], 3, 64, 512, 8, 1024, 128, 64, 64, 2);
    encode(enc, &P.xr, d_in[0], 3, 64, 2048, 8, 1024, 128, 64, 128, 1);
    P.outp = d_out;
    P.xp = (const __nv_bfloat16*)d_in[0];
    P.wphi = (const __nv_bfloat16*)d_in[2];
    P.b1 = (const __nv_bfloat16*)d_in[6];
    P.b2 = (const __nv_bfloat16*)d_in[8];
    fused_kernel<<<128, 384, SMEM_BYTES, cudaStreamPerThread>>>(P);
}
```

```cpp
#include <cuda_runtime.h>
#include <cuda_bf16.h>
#include <cuda.h>
#include <stdint.h>


namespace {

constexpr uint32_t SMEM_BASE = 1024;
constexpr int NST = 8;
constexpr int STB = 16384;
constexpr int OFF_INC = NST * STB;
constexpr int OFF_SPARE = OFF_INC + 65536;
constexpr int OFF_WBIG = OFF_SPARE + 16384;
constexpr int OFF_ONES = OFF_WBIG + 8192;
constexpr int OFF_KVB = OFF_ONES + 1024;
constexpr int OFF_B1 = OFF_KVB + 8704;
constexpr int OFF_B2 = OFF_B1 + 384;
constexpr int OFF_EP = OFF_B2 + 128;
constexpr int OFF_BAR = OFF_EP + 16;
enum { B_XFULL = 0, B_FULL = 8, B_RXA = 19, B_RXB = 21, B_RXC = 23, B_RXFREE = 25, B_MISC = 27, B_XRES = 28, B_KVRAW = 29, B_RXFREE2 = 30, B_FULLB = 32, B_TILE = 36,
       B_KVRD = 40, B_EMPTY = 42, B_DONE = 50, B_XFREE = 51, B_KVST = 53, B_PBDONE = 55, B_HAST = 56, B_KVRDY = 58, B_NUM = 59 };
constexpr int SMEM_BYTES = OFF_BAR + B_NUM * 8;
static_assert(SMEM_BYTES <= 232448, "smem");
constexpr int R_KVP = 24576;
constexpr int R_V = 16384;
constexpr int KV_FLOATS = 2176;

__device__ __align__(128) float g_kv[2][8][KV_FLOATS];
__device__ __align__(128) unsigned g_cnt[2][8][32];
__device__ unsigned g_epoch;
__device__ __align__(128) uint4 g_flag[128][8];
__device__ uint4 g_part[128 * 8 * 512];

struct Params {
    CUtensorMap x, kv, q, w1a, w1b, w2, wo, xr, w2h, woh;
    const __nv_bfloat16* wphi;
    const __nv_bfloat16* b1;
    const __nv_bfloat16* b2;
    void* outp;
    const __nv_bfloat16* xp;
};

__device__ __forceinline__ void mbar_init(uint32_t bar, uint32_t cnt) { asm volatile("mbarrier.init.shared::cta.b64 [%0], %1;" :: "r"(bar), "r"(cnt) : "memory"); }
__device__ __forceinline__ void mbar_expect_tx(uint32_t bar, uint32_t bytes) { asm volatile("mbarrier.arrive.expect_tx.shared::cta.b64 _, [%0], %1;" :: "r"(bar), "r"(bytes) : "memory"); }
__device__ __forceinline__ void mbar_arrive(uint32_t bar) { asm volatile("mbarrier.arrive.shared::cta.b64 _, [%0];" :: "r"(bar) : "memory"); }
__device__ __forceinline__ void mbar_wait(uint32_t bar, uint32_t parity) {
    asm volatile("{\n"
        ".reg .pred p;\n"
        "WL%=:\n"
        "mbarrier.try_wait.parity.shared::cta.b64 p, [%0], %1;\n"
        "@!p bra WL%=;\n"
        "}" :: "r"(bar), "r"(parity) : "memory");
}
__device__ __forceinline__ void tma3d(uint32_t dst, const CUtensorMap* tm, int c0, int c1, int c2, uint32_t bar) {
    asm volatile("cp.async.bulk.tensor.3d.shared::cluster.global.mbarrier::complete_tx::bytes [%0], [%1, {%3, %4, %5}], [%2];"
        :: "r"(dst), "l"(tm), "r"(bar), "r"(c0), "r"(c1), "r"(c2) : "memory");
}
__device__ __forceinline__ void pf3d(const CUtensorMap* tm, int c0, int c1, int c2) {
    asm volatile("cp.async.bulk.prefetch.tensor.3d.L2.global [%0, {%1, %2, %3}];" :: "l"(tm), "r"(c0), "r"(c1), "r"(c2) : "memory");
}
__device__ __forceinline__ bool elect_one() {
    uint32_t p;
    asm volatile("{ .reg .pred P; elect.sync _|P, 0xffffffff; selp.u32 %0, 1, 0, P; }" : "=r"(p));
    return p;
}
__device__ __forceinline__ void wg_fence() { asm volatile("wgmma.fence.sync.aligned;" ::: "memory"); }
__device__ __forceinline__ void wg_commit() { asm volatile("wgmma.commit_group.sync.aligned;" ::: "memory"); }
template <int N> __device__ __forceinline__ void wg_wait() { asm volatile("wgmma.wait_group.sync.aligned %0;" :: "n"(N) : "memory"); }
__device__ __forceinline__ void fence_async_smem() { asm volatile("fence.proxy.async.shared::cta;" ::: "memory"); }
__device__ __forceinline__ void bar_sync(int id, int n) { asm volatile("bar.sync %0, %1;" :: "r"(id), "r"(n) : "memory"); }
__device__ __forceinline__ void bar_arrive(int id, int n) { asm volatile("bar.arrive %0, %1;" :: "r"(id), "r"(n) : "memory"); }
__device__ __forceinline__ void ldsm4(uint32_t (&r)[4], uint32_t addr) {
    asm volatile("ldmatrix.sync.aligned.m8n8.x4.shared.b16 {%0,%1,%2,%3}, [%4];" : "=r"(r[0]), "=r"(r[1]), "=r"(r[2]), "=r"(r[3]) : "r"(addr) : "memory");
}
__device__ __forceinline__ void stsm4(uint32_t addr, uint32_t a, uint32_t b, uint32_t c, uint32_t d) {
    asm volatile("stmatrix.sync.aligned.m8n8.x4.shared.b16 [%0], {%1,%2,%3,%4};" :: "r"(addr), "r"(a), "r"(b), "r"(c), "r"(d) : "memory");
}
__device__ __forceinline__ void lds128(uint32_t (&r)[4], uint32_t addr) {
    asm volatile("ld.shared.v4.b32 {%0,%1,%2,%3}, [%4];" : "=r"(r[0]), "=r"(r[1]), "=r"(r[2]), "=r"(r[3]) : "r"(addr) : "memory");
}
__device__ __forceinline__ uint32_t lds32(uint32_t addr) { uint32_t r; asm volatile("ld.shared.b32 %0, [%1];" : "=r"(r) : "r"(addr) : "memory"); return r; }
__device__ __forceinline__ void sts128(uint32_t addr, uint32_t a, uint32_t b, uint32_t c, uint32_t d) {
    asm volatile("st.shared.v4.b32 [%0], {%1,%2,%3,%4};" :: "r"(addr), "r"(a), "r"(b), "r"(c), "r"(d) : "memory");
}
__device__ __forceinline__ void sts32(uint32_t addr, uint32_t a) { asm volatile("st.shared.b32 [%0], %1;" :: "r"(addr), "r"(a) : "memory"); }
__device__ __forceinline__ void st_async4(uint32_t addr, const uint32_t (&v)[4], uint32_t bar) {
    asm volatile("st.async.weak.shared::cluster.mbarrier::complete_tx::bytes.v4.b32 [%0], {%1,%2,%3,%4}, [%5];"
        :: "r"(addr), "r"(v[0]), "r"(v[1]), "r"(v[2]), "r"(v[3]), "r"(bar) : "memory");
}
__device__ __forceinline__ uint32_t mapa(uint32_t addr, uint32_t cta) { uint32_t r; asm("mapa.shared::cluster.u32 %0, %1, %2;" : "=r"(r) : "r"(addr), "r"(cta)); return r; }
__device__ __forceinline__ void mma_ones(float (&d)[4], const uint32_t (&a)[4]) {
    asm("mma.sync.aligned.m16n8k16.row.col.f32.bf16.bf16.f32 {%0,%1,%2,%3}, {%4,%5,%6,%7}, {%8,%8}, {%0,%1,%2,%3};"
        : "+f"(d[0]), "+f"(d[1]), "+f"(d[2]), "+f"(d[3]) : "r"(a[0]), "r"(a[1]), "r"(a[2]), "r"(a[3]), "r"(0x3F803F80u));
}
__device__ __forceinline__ uint32_t add2(uint32_t a, uint32_t b) { uint32_t r; asm("add.rn.bf16x2 %0, %1, %2;" : "=r"(r) : "r"(a), "r"(b)); return r; }
__device__ __forceinline__ uint32_t pack2(float lo, float hi) { uint32_t r; asm("cvt.rn.bf16x2.f32 %0, %1, %2;" : "=r"(r) : "f"(hi), "f"(lo)); return r; }
__device__ __forceinline__ uint32_t pack2v(float lo, float hi) { uint32_t r; asm volatile("cvt.rn.bf16x2.f32 %0, %1, %2;" : "=r"(r) : "f"(hi), "f"(lo)); return r; }
__device__ __forceinline__ float bflo(uint32_t w) { return __uint_as_float(w << 16); }
__device__ __forceinline__ float bfhi(uint32_t w) { return __uint_as_float(w & 0xffff0000u); }
__device__ __forceinline__ float rcp(float x) { float r; asm("rcp.approx.ftz.f32 %0, %1;" : "=f"(r) : "f"(x)); return r; }
__device__ __forceinline__ float rsq(float x) { float r; asm("rsqrt.approx.ftz.f32 %0, %1;" : "=f"(r) : "f"(x)); return r; }
__device__ __forceinline__ uint32_t sub2(uint32_t a, uint32_t b) { uint32_t r; asm("sub.rn.bf16x2 %0, %1, %2;" : "=r"(r) : "r"(a), "r"(b)); return r; }
__device__ __forceinline__ void wgmma_rs128_first(float (&d)[64], const uint32_t (&a)[4], uint64_t db) {
    asm volatile("{ .reg .pred p; setp.ne.b32 p, 0, 0; wgmma.mma_async.sync.aligned.m64n128k16.f32.bf16.bf16 "
        "{%0,%1,%2,%3,%4,%5,%6,%7,%8,%9,%10,%11,%12,%13,%14,%15,%16,%17,%18,%19,%20,%21,%22,%23,%24,%25,%26,%27,%28,%29,%30,%31,%32,%33,%34,%35,%36,%37,%38,%39,%40,%41,%42,%43,%44,%45,%46,%47,%48,%49,%50,%51,%52,%53,%54,%55,%56,%57,%58,%59,%60,%61,%62,%63}, {%64,%65,%66,%67}, %68, p, 1, 1, 1; }"
        : "=f"(d[0]),"=f"(d[1]),"=f"(d[2]),"=f"(d[3]),"=f"(d[4]),"=f"(d[5]),"=f"(d[6]),"=f"(d[7]),"=f"(d[8]),"=f"(d[9]),"=f"(d[10]),"=f"(d[11]),"=f"(d[12]),"=f"(d[13]),"=f"(d[14]),"=f"(d[15]),"=f"(d[16]),"=f"(d[17]),"=f"(d[18]),"=f"(d[19]),"=f"(d[20]),"=f"(d[21]),"=f"(d[22]),"=f"(d[23]),"=f"(d[24]),"=f"(d[25]),"=f"(d[26]),"=f"(d[27]),"=f"(d[28]),"=f"(d[29]),"=f"(d[30]),"=f"(d[31]),"=f"(d[32]),"=f"(d[33]),"=f"(d[34]),"=f"(d[35]),"=f"(d[36]),"=f"(d[37]),"=f"(d[38]),"=f"(d[39]),"=f"(d[40]),"=f"(d[41]),"=f"(d[42]),"=f"(d[43]),"=f"(d[44]),"=f"(d[45]),"=f"(d[46]),"=f"(d[47]),"=f"(d[48]),"=f"(d[49]),"=f"(d[50]),"=f"(d[51]),"=f"(d[52]),"=f"(d[53]),"=f"(d[54]),"=f"(d[55]),"=f"(d[56]),"=f"(d[57]),"=f"(d[58]),"=f"(d[59]),"=f"(d[60]),"=f"(d[61]),"=f"(d[62]),"=f"(d[63])
        : "r"(a[0]), "r"(a[1]), "r"(a[2]), "r"(a[3]), "l"(db));
}
__device__ __forceinline__ void wgmma_rs128(float (&d)[64], const uint32_t (&a)[4], uint64_t db) {
    asm volatile("{ .reg .pred p; setp.ne.b32 p, 1, 0; wgmma.mma_async.sync.aligned.m64n128k16.f32.bf16.bf16 "
        "{%0,%1,%2,%3,%4,%5,%6,%7,%8,%9,%10,%11,%12,%13,%14,%15,%16,%17,%18,%19,%20,%21,%22,%23,%24,%25,%26,%27,%28,%29,%30,%31,%32,%33,%34,%35,%36,%37,%38,%39,%40,%41,%42,%43,%44,%45,%46,%47,%48,%49,%50,%51,%52,%53,%54,%55,%56,%57,%58,%59,%60,%61,%62,%63}, {%64,%65,%66,%67}, %68, p, 1, 1, 1; }"
        : "+f"(d[0]),"+f"(d[1]),"+f"(d[2]),"+f"(d[3]),"+f"(d[4]),"+f"(d[5]),"+f"(d[6]),"+f"(d[7]),"+f"(d[8]),"+f"(d[9]),"+f"(d[10]),"+f"(d[11]),"+f"(d[12]),"+f"(d[13]),"+f"(d[14]),"+f"(d[15]),"+f"(d[16]),"+f"(d[17]),"+f"(d[18]),"+f"(d[19]),"+f"(d[20]),"+f"(d[21]),"+f"(d[22]),"+f"(d[23]),"+f"(d[24]),"+f"(d[25]),"+f"(d[26]),"+f"(d[27]),"+f"(d[28]),"+f"(d[29]),"+f"(d[30]),"+f"(d[31]),"+f"(d[32]),"+f"(d[33]),"+f"(d[34]),"+f"(d[35]),"+f"(d[36]),"+f"(d[37]),"+f"(d[38]),"+f"(d[39]),"+f"(d[40]),"+f"(d[41]),"+f"(d[42]),"+f"(d[43]),"+f"(d[44]),"+f"(d[45]),"+f"(d[46]),"+f"(d[47]),"+f"(d[48]),"+f"(d[49]),"+f"(d[50]),"+f"(d[51]),"+f"(d[52]),"+f"(d[53]),"+f"(d[54]),"+f"(d[55]),"+f"(d[56]),"+f"(d[57]),"+f"(d[58]),"+f"(d[59]),"+f"(d[60]),"+f"(d[61]),"+f"(d[62]),"+f"(d[63])
        : "r"(a[0]), "r"(a[1]), "r"(a[2]), "r"(a[3]), "l"(db));
}
__device__ __forceinline__ void wgmma_rs112_first(float (&d)[56], const uint32_t (&a)[4], uint64_t db) {
    asm volatile("{ .reg .pred p; setp.ne.b32 p, 0, 0; wgmma.mma_async.sync.aligned.m64n112k16.f32.bf16.bf16 "
        "{%0,%1,%2,%3,%4,%5,%6,%7,%8,%9,%10,%11,%12,%13,%14,%15,%16,%17,%18,%19,%20,%21,%22,%23,%24,%25,%26,%27,%28,%29,%30,%31,%32,%33,%34,%35,%36,%37,%38,%39,%40,%41,%42,%43,%44,%45,%46,%47,%48,%49,%50,%51,%52,%53,%54,%55}, {%56,%57,%58,%59}, %60, p, 1, 1, 1; }"
        : "=f"(d[0]),"=f"(d[1]),"=f"(d[2]),"=f"(d[3]),"=f"(d[4]),"=f"(d[5]),"=f"(d[6]),"=f"(d[7]),"=f"(d[8]),"=f"(d[9]),"=f"(d[10]),"=f"(d[11]),"=f"(d[12]),"=f"(d[13]),"=f"(d[14]),"=f"(d[15]),"=f"(d[16]),"=f"(d[17]),"=f"(d[18]),"=f"(d[19]),"=f"(d[20]),"=f"(d[21]),"=f"(d[22]),"=f"(d[23]),"=f"(d[24]),"=f"(d[25]),"=f"(d[26]),"=f"(d[27]),"=f"(d[28]),"=f"(d[29]),"=f"(d[30]),"=f"(d[31]),"=f"(d[32]),"=f"(d[33]),"=f"(d[34]),"=f"(d[35]),"=f"(d[36]),"=f"(d[37]),"=f"(d[38]),"=f"(d[39]),"=f"(d[40]),"=f"(d[41]),"=f"(d[42]),"=f"(d[43]),"=f"(d[44]),"=f"(d[45]),"=f"(d[46]),"=f"(d[47]),"=f"(d[48]),"=f"(d[49]),"=f"(d[50]),"=f"(d[51]),"=f"(d[52]),"=f"(d[53]),"=f"(d[54]),"=f"(d[55])
        : "r"(a[0]), "r"(a[1]), "r"(a[2]), "r"(a[3]), "l"(db));
}
__device__ __forceinline__ void wgmma_rs112(float (&d)[56], const uint32_t (&a)[4], uint64_t db) {
    asm volatile("{ .reg .pred p; setp.ne.b32 p, 1, 0; wgmma.mma_async.sync.aligned.m64n112k16.f32.bf16.bf16 "
        "{%0,%1,%2,%3,%4,%5,%6,%7,%8,%9,%10,%11,%12,%13,%14,%15,%16,%17,%18,%19,%20,%21,%22,%23,%24,%25,%26,%27,%28,%29,%30,%31,%32,%33,%34,%35,%36,%37,%38,%39,%40,%41,%42,%43,%44,%45,%46,%47,%48,%49,%50,%51,%52,%53,%54,%55}, {%56,%57,%58,%59}, %60, p, 1, 1, 1; }"
        : "+f"(d[0]),"+f"(d[1]),"+f"(d[2]),"+f"(d[3]),"+f"(d[4]),"+f"(d[5]),"+f"(d[6]),"+f"(d[7]),"+f"(d[8]),"+f"(d[9]),"+f"(d[10]),"+f"(d[11]),"+f"(d[12]),"+f"(d[13]),"+f"(d[14]),"+f"(d[15]),"+f"(d[16]),"+f"(d[17]),"+f"(d[18]),"+f"(d[19]),"+f"(d[20]),"+f"(d[21]),"+f"(d[22]),"+f"(d[23]),"+f"(d[24]),"+f"(d[25]),"+f"(d[26]),"+f"(d[27]),"+f"(d[28]),"+f"(d[29]),"+f"(d[30]),"+f"(d[31]),"+f"(d[32]),"+f"(d[33]),"+f"(d[34]),"+f"(d[35]),"+f"(d[36]),"+f"(d[37]),"+f"(d[38]),"+f"(d[39]),"+f"(d[40]),"+f"(d[41]),"+f"(d[42]),"+f"(d[43]),"+f"(d[44]),"+f"(d[45]),"+f"(d[46]),"+f"(d[47]),"+f"(d[48]),"+f"(d[49]),"+f"(d[50]),"+f"(d[51]),"+f"(d[52]),"+f"(d[53]),"+f"(d[54]),"+f"(d[55])
        : "r"(a[0]), "r"(a[1]), "r"(a[2]), "r"(a[3]), "l"(db));
}
__device__ __forceinline__ void wgmma_rs64_first(float (&d)[32], const uint32_t (&a)[4], uint64_t db) {
    asm volatile("{ .reg .pred p; setp.ne.b32 p, 0, 0; wgmma.mma_async.sync.aligned.m64n64k16.f32.bf16.bf16 "
        "{%0,%1,%2,%3,%4,%5,%6,%7,%8,%9,%10,%11,%12,%13,%14,%15,%16,%17,%18,%19,%20,%21,%22,%23,%24,%25,%26,%27,%28,%29,%30,%31}, {%32,%33,%34,%35}, %36, p, 1, 1, 1; }"
        : "=f"(d[0]),"=f"(d[1]),"=f"(d[2]),"=f"(d[3]),"=f"(d[4]),"=f"(d[5]),"=f"(d[6]),"=f"(d[7]),"=f"(d[8]),"=f"(d[9]),"=f"(d[10]),"=f"(d[11]),"=f"(d[12]),"=f"(d[13]),"=f"(d[14]),"=f"(d[15]),"=f"(d[16]),"=f"(d[17]),"=f"(d[18]),"=f"(d[19]),"=f"(d[20]),"=f"(d[21]),"=f"(d[22]),"=f"(d[23]),"=f"(d[24]),"=f"(d[25]),"=f"(d[26]),"=f"(d[27]),"=f"(d[28]),"=f"(d[29]),"=f"(d[30]),"=f"(d[31])
        : "r"(a[0]), "r"(a[1]), "r"(a[2]), "r"(a[3]), "l"(db));
}
__device__ __forceinline__ void wgmma_rs64(float (&d)[32], const uint32_t (&a)[4], uint64_t db) {
    asm volatile("{ .reg .pred p; setp.ne.b32 p, 1, 0; wgmma.mma_async.sync.aligned.m64n64k16.f32.bf16.bf16 "
        "{%0,%1,%2,%3,%4,%5,%6,%7,%8,%9,%10,%11,%12,%13,%14,%15,%16,%17,%18,%19,%20,%21,%22,%23,%24,%25,%26,%27,%28,%29,%30,%31}, {%32,%33,%34,%35}, %36, p, 1, 1, 1; }"
        : "+f"(d[0]),"+f"(d[1]),"+f"(d[2]),"+f"(d[3]),"+f"(d[4]),"+f"(d[5]),"+f"(d[6]),"+f"(d[7]),"+f"(d[8]),"+f"(d[9]),"+f"(d[10]),"+f"(d[11]),"+f"(d[12]),"+f"(d[13]),"+f"(d[14]),"+f"(d[15]),"+f"(d[16]),"+f"(d[17]),"+f"(d[18]),"+f"(d[19]),"+f"(d[20]),"+f"(d[21]),"+f"(d[22]),"+f"(d[23]),"+f"(d[24]),"+f"(d[25]),"+f"(d[26]),"+f"(d[27]),"+f"(d[28]),"+f"(d[29]),"+f"(d[30]),"+f"(d[31])
        : "r"(a[0]), "r"(a[1]), "r"(a[2]), "r"(a[3]), "l"(db));
}
template <uint32_t AHI, uint32_t BHI>
__device__ __forceinline__ void wgmma_ss40_first(float (&d)[20], uint32_t alo, uint32_t blo) {
    asm volatile("{ .reg .pred p; .reg .b64 da, db; setp.ne.b32 p, 0, 0; mov.b64 da, {%20, %22}; mov.b64 db, {%21, %23}; "
        "wgmma.mma_async.sync.aligned.m64n40k16.f32.bf16.bf16 "
        "{%0,%1,%2,%3,%4,%5,%6,%7,%8,%9,%10,%11,%12,%13,%14,%15,%16,%17,%18,%19}, da, db, p, 1, 1, 1, 1; }"
        : "=f"(d[0]),"=f"(d[1]),"=f"(d[2]),"=f"(d[3]),"=f"(d[4]),"=f"(d[5]),"=f"(d[6]),"=f"(d[7]),"=f"(d[8]),"=f"(d[9]),"=f"(d[10]),"=f"(d[11]),"=f"(d[12]),"=f"(d[13]),"=f"(d[14]),"=f"(d[15]),"=f"(d[16]),"=f"(d[17]),"=f"(d[18]),"=f"(d[19])
        : "r"(alo), "r"(blo), "n"(AHI), "n"(BHI));
}
template <uint32_t AHI, uint32_t BHI>
__device__ __forceinline__ void wgmma_ss40(float (&d)[20], uint32_t alo, uint32_t blo) {
    asm volatile("{ .reg .pred p; .reg .b64 da, db; setp.ne.b32 p, 1, 0; mov.b64 da, {%20, %22}; mov.b64 db, {%21, %23}; "
        "wgmma.mma_async.sync.aligned.m64n40k16.f32.bf16.bf16 "
        "{%0,%1,%2,%3,%4,%5,%6,%7,%8,%9,%10,%11,%12,%13,%14,%15,%16,%17,%18,%19}, da, db, p, 1, 1, 1, 1; }"
        : "+f"(d[0]),"+f"(d[1]),"+f"(d[2]),"+f"(d[3]),"+f"(d[4]),"+f"(d[5]),"+f"(d[6]),"+f"(d[7]),"+f"(d[8]),"+f"(d[9]),"+f"(d[10]),"+f"(d[11]),"+f"(d[12]),"+f"(d[13]),"+f"(d[14]),"+f"(d[15]),"+f"(d[16]),"+f"(d[17]),"+f"(d[18]),"+f"(d[19])
        : "r"(alo), "r"(blo), "n"(AHI), "n"(BHI));
}
template <uint32_t AHI, uint32_t BHI>
__device__ __forceinline__ void wgmma_ss24_first(float (&d)[12], uint32_t alo, uint32_t blo) {
    asm volatile("{ .reg .pred p; .reg .b64 da, db; setp.ne.b32 p, 0, 0; mov.b64 da, {%12, %14}; mov.b64 db, {%13, %15}; "
        "wgmma.mma_async.sync.aligned.m64n24k16.f32.bf16.bf16 "
        "{%0,%1,%2,%3,%4,%5,%6,%7,%8,%9,%10,%11}, da, db, p, 1, 1, 0, 1; }"
        : "=f"(d[0]),"=f"(d[1]),"=f"(d[2]),"=f"(d[3]),"=f"(d[4]),"=f"(d[5]),"=f"(d[6]),"=f"(d[7]),"=f"(d[8]),"=f"(d[9]),"=f"(d[10]),"=f"(d[11])
        : "r"(alo), "r"(blo), "n"(AHI), "n"(BHI));
}
template <uint32_t AHI, uint32_t BHI>
__device__ __forceinline__ void wgmma_ss24(float (&d)[12], uint32_t alo, uint32_t blo) {
    asm volatile("{ .reg .pred p; .reg .b64 da, db; setp.ne.b32 p, 1, 0; mov.b64 da, {%12, %14}; mov.b64 db, {%13, %15}; "
        "wgmma.mma_async.sync.aligned.m64n24k16.f32.bf16.bf16 "
        "{%0,%1,%2,%3,%4,%5,%6,%7,%8,%9,%10,%11}, da, db, p, 1, 1, 0, 1; }"
        : "+f"(d[0]),"+f"(d[1]),"+f"(d[2]),"+f"(d[3]),"+f"(d[4]),"+f"(d[5]),"+f"(d[6]),"+f"(d[7]),"+f"(d[8]),"+f"(d[9]),"+f"(d[10]),"+f"(d[11])
        : "r"(alo), "r"(blo), "n"(AHI), "n"(BHI));
}


constexpr uint32_t ONES2 = 0x3F803F80u;

__device__ __forceinline__ uint32_t fma2(uint32_t a, uint32_t b, uint32_t c) { uint32_t r; asm("fma.rn.bf16x2 %0, %1, %2, %3;" : "=r"(r) : "r"(a), "r"(b), "r"(c)); return r; }
__device__ __forceinline__ uint32_t mul2(uint32_t a, uint32_t b) { uint32_t r; asm("mul.rn.bf16x2 %0, %1, %2;" : "=r"(r) : "r"(a), "r"(b)); return r; }
__device__ __forceinline__ void norm4(uint32_t (*A)[4], uint32_t s0, uint32_t s1, uint32_t o0, uint32_t o1) {
    #pragma unroll
    for (int k = 0; k < 4; k++) { A[k][0] = fma2(A[k][0], s0, o0); A[k][1] = fma2(A[k][1], s1, o1); A[k][2] = fma2(A[k][2], s0, o0); A[k][3] = fma2(A[k][3], s1, o1); }
}
__device__ __forceinline__ void stats8(const uint32_t (*A)[4], uint32_t (&o)[4]) {
    uint32_t c[8], q[4];
    #pragma unroll
    for (int i = 0; i < 8; i++) c[i] = add2(add2(A[i & 4][i & 3], A[(i & 4) + 1][i & 3]), add2(A[(i & 4) + 2][i & 3], A[(i & 4) + 3][i & 3]));
    #pragma unroll
    for (int k = 0; k < 8; k++) {
        #pragma unroll
        for (int i = 0; i < 4; i++) q[i] = k ? fma2(A[k][i], A[k][i], q[i]) : mul2(A[k][i], A[k][i]);
    }
    o[0] = add2(add2(c[0], c[4]), add2(c[2], c[6])); o[1] = add2(add2(c[1], c[5]), add2(c[3], c[7]));
    o[2] = add2(q[0], q[2]); o[3] = add2(q[1], q[3]);
}
__host__ __device__ constexpr uint64_t desc_hi(uint32_t lbo, uint32_t sbo, uint32_t swz) { return ((uint64_t)(lbo >> 4) << 16) | ((uint64_t)(sbo >> 4) << 32) | ((uint64_t)swz << 62); }

__device__ __forceinline__ void logits_issue(const float* acc, uint32_t (&a)[4][4], float (&p)[32]) {
    constexpr uint64_t dW = (uint64_t)((SMEM_BASE + OFF_WBIG) >> 4) | desc_hi(8192, 1024, 1);
    #pragma unroll
    for (int h = 0; h < 4; h++) {
        const float* k = acc + 8 * h;
        a[h][0] = pack2(k[0], k[1]); a[h][1] = pack2(k[2], k[3]); a[h][2] = pack2(k[4], k[5]); a[h][3] = pack2(k[6], k[7]);
    }
    wg_fence();
    #pragma unroll
    for (int h = 0; h < 4; h++) { if (h == 0) wgmma_rs64_first(p, a[0], dW); else wgmma_rs64(p, a[h], dW + h * 128); }
    wg_commit();
}
__device__ __forceinline__ void kv_mma(float (&kv0)[20], float (&kv1)[20], uint32_t wg) {
    constexpr uint32_t base = SMEM_BASE + OFF_INC, AHI = (uint32_t)(desc_hi(0, 1024, 1) >> 32), BHI = (uint32_t)(desc_hi(0, 512, 2) >> 32);
    const uint32_t oa = wg * 2048, ob = wg * (2048u - (2048u << 16));
    #pragma unroll
    for (int hp = 0; hp < 2; hp++) {
        #pragma unroll
        for (int ks = 0; ks < 4; ks++) {
            const uint32_t vb = base + R_V + hp * 4096 + ks * 1024;
            const uint32_t a = oa + (((base + hp * 8192 + ks * 2048) >> 4) | (512u << 16));
            const uint32_t b = ob + ((vb >> 4) | (((SMEM_BASE + OFF_ONES - vb) >> 4) << 16));
            if (hp == 0) { if (ks == 0) wgmma_ss40_first<AHI, BHI>(kv0, a, b); else wgmma_ss40<AHI, BHI>(kv0, a, b); }
            else { if (ks == 0) wgmma_ss40_first<AHI, BHI>(kv1, a, b); else wgmma_ss40<AHI, BHI>(kv1, a, b); }
        }
        wg_commit();
    }
}
__device__ __forceinline__ void readout_mma(float (&o)[4][12], uint32_t wg) {
    constexpr uint32_t base = SMEM_BASE + OFF_INC, AHI = (uint32_t)(desc_hi(0, 1024, 1) >> 32), BHI = (uint32_t)(desc_hi(0, 256, 0) >> 32);
    const uint32_t oa = wg * 2048;
    #pragma unroll
    for (int h = 0; h < 4; h++) {
        #pragma unroll
        for (int sg = 0; sg < 2; sg++) {
            const uint32_t a = oa + (((base + (h >> 1) * 8192 + 32 * ((2 * (h & 1) + sg) ^ (h >> 1))) >> 4) | (1u << 16));
            const uint32_t b = ((SMEM_BASE + OFF_KVB + h * 2048 + sg * 768) >> 4) | (8u << 16);
            if (sg == 0) wgmma_ss24_first<AHI, BHI>(o[h], a, b); else wgmma_ss24<AHI, BHI>(o[h], a, b);
        }
    }
}
__device__ __forceinline__ void features(float (&p)[32], uint32_t addr) {
    int trip = 0;
    while (true) {
        bool ok = true;
        float e[2][16], tt[2][8];
        #pragma unroll
        for (int r = 0; r < 2; r++) {
            #pragma unroll
            for (int i = 0; i < 16; i++) asm volatile("ex2.approx.ftz.f32 %0, %1;" : "=f"(e[r][i]) : "f"(p[4 * (i >> 1) + 2 * r + (i & 1)]));
            #pragma unroll
            for (int i = 0; i < 8; i++) asm volatile("ex2.approx.ftz.f32 %0, %1;" : "=f"(tt[r][i]) : "f"(-(p[4 * i + 2 * r] + p[4 * i + 2 * r + 1])));
        }
        #pragma unroll
        for (int r = 0; r < 2; r++) {
            float s[8];
            const float* t = tt[r];
            uint32_t w[8], y[8];
            #pragma unroll
            for (int i = 0; i < 8; i++) { s[i] = e[r][2 * i] + e[r][2 * i + 1]; w[i] = pack2(e[r][2 * i], e[r][2 * i + 1]); }
            const float rp = rcp(((s[0] + s[1]) + (s[2] + s[3])) + ((s[4] + s[5]) + (s[6] + s[7])));
            const float rm = rcp(fmaf(s[0], t[0], fmaf(s[1], t[1], fmaf(s[2], t[2], s[3] * t[3]))) + fmaf(s[4], t[4], fmaf(s[5], t[5], fmaf(s[6], t[6], s[7] * t[7]))));
            const uint32_t r2 = pack2(rp, rp);
            #pragma unroll
            for (int i = 0; i < 8; i += 2) {
                const uint32_t c = pack2(t[i] * rm, t[i + 1] * rm);
                asm("{ .reg .b16 l, h; .reg .b32 x, z; mov.b32 {l, h}, %4; mov.b32 x, {l, l}; mov.b32 z, {h, h}; mul.rn.bf16x2 %0, %2, x; mul.rn.bf16x2 %1, %3, z; }"
                    : "=r"(y[i]), "=r"(y[i + 1]) : "r"(w[i]), "r"(w[i + 1]), "r"(c));
            }
            sts128(addr + 1024 * r, mul2(w[0], r2), mul2(w[1], r2), mul2(w[2], r2), mul2(w[3], r2));
            sts128((addr ^ 16) + 1024 * r, mul2(w[4], r2), mul2(w[5], r2), mul2(w[6], r2), mul2(w[7], r2));
            asm volatile("{ .reg .pred k; setp.eq.b32 k, %10, 0; @k st.shared.v4.b32 [%0], {%2,%3,%4,%5}; @k st.shared.v4.b32 [%1], {%6,%7,%8,%9}; }"
                :: "r"((addr ^ 32) + 1024 * r), "r"((addr ^ 48) + 1024 * r), "r"(y[0]), "r"(y[1]), "r"(y[2]), "r"(y[3]),
                   "r"(y[4]), "r"(y[5]), "r"(y[6]), "r"(y[7]), "r"(trip) : "memory");
            ok = ok & (rp > 0x1p-40f) & (rm > 0x1p-40f);
        }
        if ((trip == 2) | ((trip == 0) & ok)) break;
        if (trip == 1) {
            #pragma unroll
            for (int i = 0; i < 32; i += 2) { const float a = p[i]; p[i] = -p[i + 1]; p[i + 1] = -a; }
            addr ^= 32;
        }
        float m0 = p[0], m1 = p[2];
        #pragma unroll
        for (int i = 0; i < 32; i++) { if (i & 2) m1 = fmaxf(m1, p[i]); else m0 = fmaxf(m0, p[i]); }
        #pragma unroll
        for (int i = 0; i < 32; i++) p[i] -= (i & 2) ? m1 : m0;
        trip++;
    }
    __syncwarp();
}
__device__ __forceinline__ uint32_t gelu2(uint32_t h) {
    uint32_t u = mul2(h, fma2(mul2(h, h), 0x3E923E92u, 0x3FCC3FCCu));
    asm("tanh.approx.bf16x2 %0, %0;" : "+r"(u));
    return fma2(h, u, h);
}
__device__ __forceinline__ void pre_gelu(uint32_t (&o)[4], const float* a, uint32_t ba, uint32_t bb) {
    o[0] = fma2(pack2v(a[0], a[1]), 0x3F003F00u, ba); o[1] = fma2(pack2v(a[2], a[3]), 0x3F003F00u, ba);
    o[2] = fma2(pack2v(a[4], a[5]), 0x3F003F00u, bb); o[3] = fma2(pack2v(a[6], a[7]), 0x3F003F00u, bb);
}
__device__ __forceinline__ void gelu4(uint32_t (&o)[4]) { o[0] = gelu2(o[0]); o[1] = gelu2(o[1]); o[2] = gelu2(o[2]); o[3] = gelu2(o[3]); }
__device__ __forceinline__ void release(uint32_t sb, int s, int lane) {
    if (lane == 0) mbar_arrive(sb + OFF_BAR + (B_EMPTY + s) * 8);
}
__device__ __forceinline__ void wait_full(uint32_t sb, int s, int pass) { mbar_wait(sb + OFF_BAR + (B_FULL + (s < 7 ? s : 7 + pass)) * 8, s < 7 ? pass & 1 : 0); }

__device__ __forceinline__ void store_kv(const float (&kv)[20], uint32_t o, uint32_t zo, bool hi, int t) {
    #pragma unroll
    for (int nt = 0; nt < 2; nt++)
        sts128(o + nt * 512, __float_as_uint(hi ? kv[8 + 4 * nt] : kv[4 * nt]), __float_as_uint(hi ? kv[9 + 4 * nt] : kv[1 + 4 * nt]),
               __float_as_uint(hi ? kv[10 + 4 * nt] : kv[2 + 4 * nt]), __float_as_uint(hi ? kv[11 + 4 * nt] : kv[3 + 4 * nt]));
    if (t == 0) { sts32(zo, __float_as_uint(kv[16])); sts32(zo + 32, __float_as_uint(kv[18])); }
}
template <int N>
__device__ __forceinline__ void pack_tile(uint32_t (&p)[N][4], const float* acc, uint32_t tag) {
    #pragma unroll
    for (int i = 0; i < N; i++) {
        asm("lop3.b32 %0, %1, %2, 1, 0xD8;" : "=r"(p[i][0]) : "r"(pack2(acc[8 * i + 0], acc[8 * i + 1])), "r"(tag));
        p[i][1] = pack2(acc[8 * i + 2], acc[8 * i + 3]);
        p[i][2] = pack2(acc[8 * i + 4], acc[8 * i + 5]);
        p[i][3] = pack2(acc[8 * i + 6], acc[8 * i + 7]);
    }
}
__device__ __forceinline__ void stg128(uint4* dst, const uint32_t (&p)[4]) {
    asm volatile("st.relaxed.gpu.global.v4.b32 [%0], {%1,%2,%3,%4};" :: "l"(dst), "r"(p[0]), "r"(p[1]), "r"(p[2]), "r"(p[3]) : "memory");
}
__device__ __forceinline__ void set_flag(uint4* flag, int w, uint32_t fv, int lane) {
    if (lane == 0) asm volatile("st.relaxed.gpu.global.u32 [%0], %1;" :: "l"((uint32_t*)flag + w), "r"(fv) : "memory");
}
template <int N>
__device__ __forceinline__ void check_tile(uint32_t (&v)[N][4], const uint4* src, uint32_t tag) {
    while (true) {
        uint32_t bad = 0;
        #pragma unroll
        for (int i = 0; i < N; i++) asm("lop3.b32 %0, %0, %1, %2, 0xF6;" : "+r"(bad) : "r"(v[i][0]), "r"(tag));
        if (!__any_sync(0xffffffffu, bad & 1)) break;
        #pragma unroll
        for (int i = 0; i < N; i++)
            asm volatile("ld.relaxed.gpu.global.v4.b32 {%0,%1,%2,%3}, [%4];" : "=r"(v[i][0]), "=r"(v[i][1]), "=r"(v[i][2]), "=r"(v[i][3]) : "l"(src + i * 128) : "memory");
    }
}

#define MMA_STAGE(PASS, SPLIT, BODY)                                                       \
    if (s == 0) wait_full(sb, 0, PASS);                                                    \
    wg_fence();                                                                            \
    _Pragma("unroll")                                                                      \
    for (int k = 0; k < 4; k++) {                                                          \
        const uint64_t d = dB + (uint64_t)(((s == 7 && ((PASS) & 1) ? OFF_SPARE : s * STB) + k * 2048) >> 4); \
        BODY;                                                                              \
        if (SPLIT && s == 0 && k == 1) wg_commit();                                        \
    }                                                                                      \
    wg_commit();                                                                           \
    if (s == 7) bar_arrive(6 - wg, 256);                    \
    if (s > 1) release(sb, s - 2, lane);                                                   \
    if (s < 7) wait_full(sb, s + 1, PASS)
#define STAGE_END(SPLIT)                                                                   \
    if (s > 0 || SPLIT) wg_wait<1>();                                                      \
    if (s == 7) release(sb, 6, lane)
#define G2_A(s, k) ((s) < 2 ? Ha[4 * ((s) & 1) + (k)] : (s) < 4 ? Pa[4 * ((s) & 1) + (k)] : (s) < 6 ? Hb[3 * ((s) & 1) + (k)] : Pb[3 * ((s) & 1) + (k)])
#define G2_HAS(s, k) ((k) < 3 || ((s) != 4 && (s) != 6))

__global__ void __cluster_dims__(2, 1, 1) __launch_bounds__(384, 1)
fused_kernel(const __grid_constant__ Params P) {
    extern __shared__ __align__(1024) uint8_t smem_raw[];
    const uint32_t sb = (uint32_t)__cvta_generic_to_shared(smem_raw);
    const int tid = threadIdx.x, warp = tid >> 5, lane = tid & 31;
    const int k0 = blockIdx.x >> 1, i7 = ((k0 - 36) * 37) >> 8;
    const int G = k0 < 4 ? 0 : k0 < 36 ? (k0 - 4) & 7 : k0 - 35 - 7 * i7, gi = k0 < 4 ? k0 : k0 < 36 ? (k0 - 4) >> 3 : i7;
    unsigned role = 16 * (G >> 1) + (k0 >= 4 && k0 < 36 ? 0 : 8) + 4 * (gi >> 1) + 2 * (G & 1) + (gi & 1);
    asm volatile("" : "+r"(role));
    const int m = (role >> 2) & 15, c = role & 3, r = blockIdx.x & 1, j = 2 * c + r, cc = c >> 1;
    const uint32_t bar = sb + OFF_BAR;

    if (warp >= 8) {
        asm volatile("setmaxnreg.dec.sync.aligned.u32 24;");
        if (warp == 8) {
            const bool el = elect_one();
            if (el) {
                #pragma unroll
                for (int i = 4; i < B_NUM; i++) mbar_init(bar + i * 8, i == B_MISC ? 3 : i < B_EMPTY ? 1 : i < B_XFREE ? 8 : i < B_KVRDY ? 4 : 2);
                #pragma unroll
                for (int i = B_RXA; i < B_RXFREE; i++) mbar_expect_tx(bar + i * 8, i < B_RXB ? 16384 : i < B_RXC ? 6144 : 8192);
                asm volatile("fence.mbarrier_init.release.cluster;" ::: "memory");
            }
            __syncwarp();
            bar_arrive(0, 384);
            asm volatile("barrier.cluster.arrive.relaxed.aligned;" ::: "memory");
            if (el) {
                #pragma unroll 1
                for (int n = 0, s = 0, i = 0; n < 8; n++) {
                    if ((0x1B >> n) & 1) {
                        mbar_expect_tx(bar + (B_XFULL + 4 + i) * 8, STB);
                        tma3d(sb + OFF_INC + i * STB, &P.x, 0, m * 128 + 64, 2 * i, bar + (B_XFULL + 4 + i) * 8);
                        i++;
                    } else {
                        mbar_expect_tx(bar + (B_FULL + s) * 8, STB);
                        tma3d(sb + s * STB, &P.kv, 64 * j, 64 * s, 1, bar + (B_FULL + s) * 8);
                        s++;
                    }
                }
                mbar_wait(bar + B_XFREE * 8, 0);
                #pragma unroll 1
                for (int s = 4; s < 8; s++) {
                    mbar_expect_tx(bar + (B_FULL + s) * 8, STB);
                    tma3d(sb + s * STB, &P.kv, 64 * j, 64 * s, 1, bar + (B_FULL + s) * 8);
                }
                if (m < 8) pf3d(&P.w1a, 176 * j, 64 * m, 0);
                else { pf3d(&P.q, 64 * j, 64 * (m - 8), 0); pf3d(&P.w1b, 176 * j + 128, 64 * (m - 8), 0); }
                mbar_wait(bar + (B_FULL + 7) * 8, 0);
                #pragma unroll 1
                for (int n = -1; n < 7; n++) {
                    const uint32_t fb = bar + (B_FULL + (n < 0 ? 8 : n)) * 8;
                    if (n >= 0) mbar_wait(bar + (B_EMPTY + n) * 8, 0);
                    mbar_expect_tx(fb, STB);
                    tma3d(n < 0 ? sb + OFF_SPARE : sb + n * STB, &P.w1a, 176 * j, 64 * (n & 7), 0, fb);
                }
                {
                    const int s = m & 7, jj = j ^ ((s >> 1) & 1), ch = 4 * r + 2 * (m >> 3);
                    if (s == 5 || s == 7) pf3d(&P.wo, 0, 64 * jj, ch);
                    else pf3d(&P.w2, 0, 176 * jj + (s < 4 ? 64 * (s & 1) : 128), ch);
                }
                #pragma unroll 1
                for (int n = -1; n < 7; n++) {
                    const int s = n & 7;
                    const uint32_t fb = bar + (B_FULL + (n < 0 ? 9 : n)) * 8;
                    mbar_wait(bar + (B_EMPTY + s) * 8, n >= 0);
                    mbar_expect_tx(fb, STB);
                    tma3d(sb + s * STB, &P.q, 64 * j, 64 * s, 0, fb);
                    tma3d(sb + s * STB + 8192, &P.w1b, 176 * j + 128, 64 * s, 0, fb);
                }
                #pragma unroll 1
                for (int g = 0; g < 2; g++) {
                    mbar_wait(bar + (B_HAST + g) * 8, 0);
                    mbar_wait(bar + (B_RXFREE + g) * 8, 0);
                    asm volatile("cp.async.bulk.shared::cluster.shared::cta.mbarrier::complete_tx::bytes [%0], [%1], 16384, [%2];"
                        :: "r"(mapa(sb + OFF_INC + g * 32768, r ^ 1)), "r"(sb + OFF_INC + g * 32768 + 16384), "r"(mapa(bar + (B_RXA + g) * 8, r ^ 1)) : "memory");
                    if (g == 0) {
                        mbar_wait(bar + (B_EMPTY + 7) * 8, 1);
                        mbar_expect_tx(bar + (B_FULL + 10) * 8, STB);
                        tma3d(sb + OFF_SPARE, &P.wo, 0, 64 * (j ^ 1), 4 * r + 2 * (cc ^ 1), bar + (B_FULL + 10) * 8);
                    }
                }
                #pragma unroll 1
                for (int s = 0; s < 8; s += 2) {
                    const int jj = j ^ ((s >> 1) & 1), ch = 4 * r + 2 * (cc ^ 1);
                    const uint32_t fb = bar + (B_FULL + s) * 8;
                    mbar_wait(bar + (B_EMPTY + s) * 8, 0);
                    mbar_expect_tx(fb, STB);
                    tma3d(sb + s * STB, &P.w2, 0, 176 * jj + 32 * (s & 4), ch, fb);
                    mbar_wait(bar + (B_EMPTY + s + 1) * 8, 0);
                    if (s < 6) {
                        mbar_expect_tx(fb + 8, STB);
                        tma3d(sb + (s + 1) * STB, s < 4 ? &P.w2 : &P.wo, 0, s < 4 ? 176 * jj + 64 : 64 * jj, ch, fb + 8);
                    }
                }
                mbar_expect_tx(bar + B_XRES * 8, STB);
                tma3d(sb + 7 * STB, &P.xr, 0, m * 128, 4 * r + c, bar + B_XRES * 8);
                #pragma unroll 1
                for (int q = 0; q < 4; q++) {
                    const int jj = j ^ (q & 1), ch = 4 * r + (c ^ (q >> 1) ^ 1);
                    const uint32_t dst = q ? sb + (2 * q - 2) * STB : sb + OFF_INC, fb = bar + (B_FULLB + q) * 8;
                    if (q) mbar_wait(bar + (B_EMPTY + 2 * q - 2) * 8, 1); else mbar_wait(bar + B_PBDONE * 8, 0);
                    mbar_expect_tx(fb, 30720);
                    tma3d(dst, &P.w2h, 0, 176 * jj, ch, fb);
                    if (q) mbar_wait(bar + (B_EMPTY + 2 * q - 1) * 8, 1);
                    tma3d(dst + 11264, &P.w2h, 0, 176 * jj + 88, ch, fb);
                    tma3d(dst + 22528, &P.woh, 0, 64 * jj, ch, fb);
                }
            }
        } else if (warp == 11) {
            asm volatile("barrier.cluster.arrive.relaxed.aligned;" ::: "memory");
            if (lane == 0) asm volatile("prefetch.tensormap [%0];" :: "l"(&P.kv) : "memory");
            bar_sync(0, 384);
            if (lane < 8) {
                const CUtensorMap* tm = &P.q + lane;
                asm volatile("prefetch.tensormap [%0];" :: "l"(tm) : "memory");
            }
            if ((sb & 0x3FFFF) != SMEM_BASE) __trap();
            sts128(sb + OFF_ONES + lane * 16, ONES2, ONES2, ONES2, ONES2);
            sts128(sb + OFF_ONES + 512 + lane * 16, ONES2, ONES2, ONES2, ONES2);
            uint32_t bv[3];
            #pragma unroll
            for (int u = 0; u < 3; u++) bv[u] = (lane + 32 * u < 88 && 88 * j + lane + 32 * u < 688) ? __ldg((const uint32_t*)P.b1 + 88 * j + lane + 32 * u) : 0u;
            const uint32_t b2v = __ldg((const uint32_t*)(P.b2 + 256 * r + 64 * c) + lane);
            #pragma unroll
            for (int u = 0; u < 3; u++) {
                const int idx = lane + 32 * u;
                if (idx < 88) sts32(sb + OFF_B1 + (idx & 3) * 96 + (idx >> 2) * 4, mul2(bv[u], 0x3F003F00u));
            }
            sts32(sb + OFF_B2 + (lane & 3) * 32 + (lane >> 2) * 4, b2v);
            fence_async_smem();
            __syncwarp();
            if (lane == 0) {
                mbar_arrive(bar + B_MISC * 8);
            }
            if (lane == 0) {
                unsigned long long t0, t1;
                asm volatile("mov.u64 %0, %globaltimer;" : "=l"(t0));
                while (true) {
                    uint32_t ok;
                    asm volatile("{ .reg .pred p; mbarrier.try_wait.parity.shared::cta.b64 p, [%1], 0, 1000000; selp.u32 %0, 1, 0, p; }" : "=r"(ok) : "r"(bar + B_DONE * 8) : "memory");
                    if (ok) break;
                    asm volatile("mov.u64 %0, %globaltimer;" : "=l"(t1));
                    if (t1 - t0 > 2000000000ull) __trap();
                }
            }
        } else {
            const int g = warp - 9;
            asm volatile("barrier.cluster.arrive.relaxed.aligned;" ::: "memory");
            bar_sync(0, 384);
            unsigned ep;
            asm volatile("ld.relaxed.gpu.global.u32 %0, [%1];" : "=r"(ep) : "l"(&g_epoch) : "memory");
            {
                uint32_t v[8];
                #pragma unroll
                for (int u = 0; u < 8; u++) asm volatile("ld.global.nc.u32 %0, [%1];" : "=r"(v[u]) : "l"((const uint32_t*)P.wphi + j * 512 + g * 256 + u * 32 + lane) : "memory");
                #pragma unroll
                for (int u = 0; u < 8; u++) {
                    const int row = u * 4 + (lane >> 3);
                    const uint32_t wv = pack2(bflo(v[u]) * 1.4426950408889634f, bfhi(v[u]) * 1.4426950408889634f);
                    const uint32_t lo = g ? 0u : wv, hi = g ? wv : 0u;
                    sts128(sb + OFF_WBIG + g * 4096 + row * 128 + (((lane ^ row) & 7) << 4), u < 4 ? lo : 0u, u < 4 ? 0u : lo, u < 4 ? hi : 0u, u < 4 ? 0u : hi);
                }
                fence_async_smem();
                __syncwarp();
                if (lane == 0) mbar_arrive(bar + B_MISC * 8);
            }
            const float* kvg = g_kv[ep & 1][j];
            unsigned* cnt = &g_cnt[ep & 1][j][0];
            {
                float4* z = (float4*)&g_kv[(ep + 1) & 1][j][m * 136];
                if (lane < 18 - 2 * g) z[g * 18 + lane] = make_float4(0.f, 0.f, 0.f, 0.f);
                if (m == 0 && lane < 8) g_cnt[(ep + 1) & 1][j][lane] = 0;
            }
            asm volatile("barrier.cluster.wait.acquire.aligned;" ::: "memory");
            if (lane == 0) {
                sts32(sb + OFF_EP, ep);
                mbar_wait(bar + (B_KVST + g) * 8, 0);
                asm volatile("cp.reduce.async.bulk.global.shared::cta.bulk_group.add.f32 [%0], [%1], 8192;"
                    :: "l"(kvg), "r"(sb + OFF_INC + g * 32768 + R_KVP) : "memory");
                asm volatile("cp.reduce.async.bulk.global.shared::cta.bulk_group.add.f32 [%0], [%1], 512;"
                    :: "l"(kvg + 2048), "r"(sb + OFF_KVB + g * 512) : "memory");
                asm volatile("cp.async.bulk.commit_group;" ::: "memory");
                asm volatile("cp.async.bulk.wait_group.read 0;" ::: "memory");
                mbar_arrive(bar + (B_KVRD + g) * 8);
                asm volatile("mbarrier.arrive.relaxed.cluster.shared::cluster.b64 _, [%0];" :: "r"(mapa(bar + (B_RXFREE + g) * 8, r ^ 1)) : "memory");
                asm volatile("cp.async.bulk.wait_group 0;" ::: "memory");
                asm volatile("red.relaxed.gpu.global.add.u32 [%0], 1;" :: "l"(cnt) : "memory");
                if (g == 1) {
                    unsigned v;
                    do { asm volatile("ld.relaxed.gpu.global.u32 %0, [%1];" : "=r"(v) : "l"(cnt) : "memory"); } while (v < 32);
                    asm volatile("fence.proxy.async.global;" ::: "memory");
                    mbar_expect_tx(bar + B_KVRAW * 8, KV_FLOATS * 4);
                    asm volatile("cp.async.bulk.shared::cluster.global.mbarrier::complete_tx::bytes [%0], [%1], %2, [%3];"
                        :: "r"(sb + OFF_KVB), "l"(kvg), "r"(KV_FLOATS * 4), "r"(bar + B_KVRAW * 8) : "memory");
                }
            }
            __syncwarp();
            mbar_wait(bar + B_KVRAW * 8, 0);
            {
                uint32_t kb = sb + OFF_KVB + g * 4096 + lane * 16, zs = sb + OFF_KVB + 8192 + g * 256 + lane * 4;
                #pragma unroll 1
                for (int h = 0; h < 2; h++, kb += 2048, zs += 128) {
                    uint32_t w[8];
                    #pragma unroll
                    for (int u = 0; u < 4; u += 2) {
                        uint32_t v[4], y[4];
                        lds128(v, kb + u * 512); lds128(y, kb + u * 512 + 512);
                        w[2 * u] = pack2v(__uint_as_float(v[0]), __uint_as_float(v[1])); w[2 * u + 1] = pack2v(__uint_as_float(v[2]), __uint_as_float(v[3]));
                        w[2 * u + 2] = pack2v(__uint_as_float(y[0]), __uint_as_float(y[1])); w[2 * u + 3] = pack2v(__uint_as_float(y[2]), __uint_as_float(y[3]));
                    }
                    const float z = __uint_as_float(lds32(zs));
                    __syncwarp();
                    stsm4(kb, w[0], w[1], w[2], w[3]);
                    stsm4(kb + 768, w[4], w[5], w[6], w[7]);
                    const uint32_t zw = pack2(z, z);
                    sts128(kb + 512 + (lane >> 4) * 512, zw, zw, zw, zw);
                }
            }
            fence_async_smem();
            __syncwarp();
            if (lane == 0) mbar_arrive(bar + B_KVRDY * 8);
            const uint32_t* fp = (const uint32_t*)&g_flag[m * 8 + j][g * 3] + (lane < 12 ? lane : 0);
            const uint32_t xb = sb + (g ? OFF_INC + 40960 : OFF_WBIG);
            int state = 1;
            while (true) {
                uint32_t f;
                asm volatile("ld.relaxed.gpu.global.u32 %0, [%1];" : "=r"(f) : "l"(fp) : "memory");
                const uint32_t missing = __ballot_sync(0xffffffffu, f != ep + 1);
                #pragma unroll 1
                for (int late = 1; late >= 0; late--) {
                    if ((missing & (late ? 0xF : 0xFF0)) || (state & (2 << late))) continue;
                    state |= 2 << late;
                    if (!late) { const unsigned t0 = clock(); while ((unsigned)clock() - t0 < 200) {} }
                    mbar_wait(bar + B_PBDONE * 8, 0);
                    mbar_wait(bar + (B_EMPTY + ((late | g) ? 6 : 0)) * 8, 1);
                    if (elect_one()) {
                        const uint32_t bytes = late ? 8192 : 16384, tbar = bar + (B_TILE + 2 * late + g) * 8;
                        mbar_expect_tx(tbar, bytes);
                        asm volatile("cp.async.bulk.shared::cluster.global.mbarrier::complete_tx::bytes [%0], [%1], %2, [%3];"
                            :: "r"(late ? sb + 6 * STB + g * 65536 : xb), "l"(g_part + (size_t)((m * 8 + j) * 8 + g * 3 + 1 - late) * 512), "r"(bytes), "r"(tbar) : "memory");
                    }
                    __syncwarp();
                }
                if (state == 7) break;
                mbar_wait(bar + B_PBDONE * 8, 0);
            }
        }
    } else {
        const bool el0 = elect_one();
        if (warp == 1 || warp == 2) asm volatile("prefetch.global.L2 [%0];" :: "l"(P.xp + (m * 128 + 8 * j) * 512 + (tid - 32) * 64) : "memory");
        if (el0 && warp == 0) {
            #pragma unroll
            for (int i = 0; i < 4; i++) mbar_init(bar + (B_XFULL + i) * 8, 1);
            asm volatile("fence.mbarrier_init.release.cluster;" ::: "memory");
            #pragma unroll
            for (int i = 0; i < 4; i++) {
                mbar_expect_tx(bar + (B_XFULL + i) * 8, STB);
                tma3d(sb + (4 + i) * STB, &P.x, 0, m * 128, 2 * i, bar + (B_XFULL + i) * 8);
            }
        }
        __syncwarp();
        asm volatile("barrier.cluster.arrive.relaxed.aligned;" ::: "memory");
        asm volatile("setmaxnreg.inc.sync.aligned.u32 240;");
        bar_sync(0, 384);
        const int wg = __shfl_sync(0xffffffffu, warp >> 2, 0), w = warp & 3, t = lane & 3, g = lane >> 2, tw = tid & 127;
        const uint32_t reg = sb + OFF_INC + wg * 32768;
        const int lrow = 16 * w + (lane & 15);
        const uint32_t swz = ((lane >> 4) ^ (lane & 7)) << 4;
        const uint32_t phia = reg + (t >> 1) * 8192 + (16 * w + g) * 128 + (((4 * (t & 1)) ^ (t & 2) ^ g) << 4);
        constexpr uint64_t dB = (uint64_t)(SMEM_BASE >> 4) | desc_hi(8192, 1024, 1);

        uint32_t A[32][4];
        {
            const uint32_t xst = sb + (wg ? OFF_INC : 4 * STB) + lrow * 128;
            #define LOADX(b, i) do { mbar_wait(bar + (B_XFULL + (b) + (i)) * 8, 0); \
                _Pragma("unroll") for (int k = 8 * (i); k < 8 * (i) + 8; k++) ldsm4(A[k], xst + (k >> 2) * 8192 + (swz ^ (32 * (k & 3)))); } while (0)
            uint32_t sc0, sc1, of0, of1;
            float base0 = 0.f, base1 = 0.f;
            bool centred = false;
            while (true) {
                float st[4];
                if (wg == 0) {
                    float s4[4][4], q4[4];
                    #pragma unroll
                    for (int i = 0; i < 4; i++) { s4[0][i] = 0.f; s4[1][i] = 0.f; s4[2][i] = 0.f; s4[3][i] = 0.f; q4[i] = 0.f; }
                    LOADX(0, 0);
                    #pragma unroll
                    for (int i = 0; i < 4; i++) {
                        if (i < 3) LOADX(0, i + 1);
                        uint32_t c[4];
                        #pragma unroll
                        for (int k = 8 * i; k < 8 * i + 8; k++) {
                            mma_ones(s4[k & 3], A[k]);
                            #pragma unroll
                            for (int e = 0; e < 4; e++) c[e] = (k & 7) ? fma2(A[k][e], A[k][e], c[e]) : mul2(A[k][e], A[k][e]);
                        }
                        mma_ones(q4, c);
                    }
                    st[0] = (s4[0][0] + s4[1][0]) + (s4[2][0] + s4[3][0]); st[1] = (s4[0][2] + s4[1][2]) + (s4[2][2] + s4[3][2]); st[2] = q4[0]; st[3] = q4[2];
                } else {
                    uint32_t ps[4][4];
                    LOADX(4, 0); LOADX(4, 1); LOADX(4, 2); LOADX(4, 3);
                    #pragma unroll
                    for (int i = 0; i < 4; i++) stats8(A + 8 * i, ps[i]);
                    #pragma unroll
                    for (int i = 0; i < 4; i++) {
                        const uint32_t y = add2(ps[0][i], ps[1][i]), z = add2(ps[2][i], ps[3][i]);
                        st[i] = (bflo(y) + bfhi(y)) + (bflo(z) + bfhi(z));
                    }
                    #pragma unroll
                    for (int o = 1; o <= 2; o <<= 1) {
                        #pragma unroll
                        for (int i = 0; i < 4; i++) st[i] += __shfl_xor_sync(0xffffffffu, st[i], o);
                    }
                }
                const float mean0 = st[0] * (1.f / 512.f), mean1 = st[1] * (1.f / 512.f), q0 = st[2] * (1.f / 512.f), q1 = st[3] * (1.f / 512.f);
                const float var0 = fmaf(-mean0, mean0, q0), var1 = fmaf(-mean1, mean1, q1);
                const float rs0 = rsq(fmaxf(var0, 0.f) + 1e-5f), rs1 = rsq(fmaxf(var1, 0.f) + 1e-5f);
                const uint32_t mb = pack2(base0 + mean0, base1 + mean1);
                sc0 = pack2(rs0, rs0); sc1 = pack2(rs1, rs1);
                const float d0 = (base0 - bflo(mb)) * bflo(sc0), d1 = (base1 - bfhi(mb)) * bflo(sc1);
                of0 = pack2(d0, d0); of1 = pack2(d1, d1);
                if (centred || !__any_sync(0xffffffffu, !(var0 >= 0.5f * q0) || !(var1 >= 0.5f * q1))) break;
                base0 = bflo(mb); base1 = bfhi(mb);
                const uint32_t m0 = pack2(base0, base0), m1 = pack2(base1, base1);
                #pragma unroll 1
                for (int k = 0; k < 32; k++) {
                    const uint32_t a = xst + (k >> 2) * 8192 + (swz ^ (32 * (k & 3)));
                    uint32_t v[4];
                    ldsm4(v, a);
                    stsm4(a, sub2(v[0], m0), sub2(v[1], m1), sub2(v[2], m0), sub2(v[3], m1));
                }
                fence_async_smem();
                __syncwarp();
                centred = true;
            }
            if (lane == 0) mbar_arrive(bar + (B_XFREE + wg) * 8);
            norm4(A, sc0, sc1, of0, of1);
            if (wg == 1) bar_sync(6, 256);
            float acc[64];
            #pragma unroll
            for (int s = 0; s < 8; s++) {
                MMA_STAGE(0, true, if (s == 0 && k == 0) wgmma_rs128_first(acc, A[0], d); else wgmma_rs128(acc, A[4 * s + k], d));
                if (s < 7) norm4(A + 4 * s + 4, sc0, sc1, of0, of1);
                STAGE_END(true);
            }
            mbar_wait(bar + B_MISC * 8, 0);
            wg_wait<0>();
            release(sb, 7, lane);

            float p[32];
            uint32_t ka[4][4];
            logits_issue(acc, ka, p);
            mbar_wait(bar + (B_XFREE + 1) * 8, 0);
            {
                const uint32_t va = reg + R_V + lrow * 64 + (((lane >> 4) ^ ((lane >> 1) & 3)) << 4);
                #pragma unroll
                for (int h = 0; h < 4; h++) {
                    const float* v = acc + 32 + 8 * h;
                    stsm4((va ^ (32 * (h & 1))) + (h >> 1) * 4096, pack2v(v[0], v[1]), pack2v(v[2], v[3]), pack2v(v[4], v[5]), pack2v(v[6], v[7]));
                }
            }
            wg_wait<0>();
            features(p, phia);
            fence_async_smem();
            bar_sync(1 + wg, 128);
            float kv0[20], kv1[20];
            wg_fence();
            kv_mma(kv0, kv1, wg);
            const uint32_t kvo = reg + R_KVP + lane * 16, zo = sb + OFF_KVB + wg * 512 + (w * 16 + g) * 4;
            wg_wait<1>();
            store_kv(kv0, kvo + w * 1024, zo, w >> 1, t);
            wg_wait<0>();
            store_kv(kv1, kvo + 4096 + (w ^ 1) * 1024, (zo ^ 64) + 256, w >> 1, t);
            fence_async_smem();
            __syncwarp();
            if (lane == 0) mbar_arrive(bar + (B_KVST + wg) * 8);
        }
        const uint32_t rreg = mapa(reg + tw * 16, r ^ 1);
        uint32_t Ha[8][4];
        {
            float acc[64];
            bar_sync(5 + wg, 256);
            #pragma unroll
            for (int s = 0; s < 8; s++) {
                MMA_STAGE(1, true, if (s == 0 && k == 0) wgmma_rs128_first(acc, A[0], d); else wgmma_rs128(acc, A[4 * s + k], d));
                STAGE_END(true);
            }
            mbar_wait(bar + (B_KVRD + wg) * 8, 0);
            uint32_t bw[4][4];
            #pragma unroll
            for (int i = 0; i < 4; i++) lds128(bw[i], sb + OFF_B1 + t * 96 + i * 16);
            wg_wait<0>();
            release(sb, 7, lane);
            #pragma unroll
            for (int i = 7; i >= 0; i--) {
                pre_gelu(Ha[i], acc + 8 * i, bw[i >> 1][2 * (i & 1)], bw[i >> 1][2 * (i & 1) + 1]);
                gelu4(Ha[i]);
                sts128(reg + tw * 16 + (8 + i) * 2048, Ha[i][0], Ha[i][1], Ha[i][2], Ha[i][3]);
            }
            fence_async_smem();
            __syncwarp();
            if (lane == 0) mbar_arrive(bar + (B_HAST + wg) * 8);
        }
        uint32_t Hb[7][4];
        uint32_t Pa[8][4], Pb[7][4];
        {
            float acc[56];
            bar_sync(5 + wg, 256);
            #pragma unroll
            for (int s = 0; s < 8; s++) {
                MMA_STAGE(2, true, if (s == 0 && k == 0) wgmma_rs112_first(acc, A[0], d); else wgmma_rs112(acc, A[4 * s + k], d));
                if (s >= 2 && s < 6) { lds128(Ha[2 * s - 4], reg + tw * 16 + (2 * s + 4) * 2048); lds128(Ha[2 * s - 3], reg + tw * 16 + (2 * s + 5) * 2048); }
                if (s == 6) mbar_wait(bar + (B_RXA + wg) * 8, 0);
                if (s >= 6) {
                    #pragma unroll
                    for (int i = 4 * s - 24; i < 4 * s - 20; i++) lds128(Pa[i], reg + i * 2048 + tw * 16);
                }
                STAGE_END(true);
            }
            wg_wait<0>();
            release(sb, 7, lane);
            float p[32];
            uint32_t qa[4][4];
            logits_issue(acc, qa, p);
            bar_sync(1 + wg, 128);
            if (tw == 0) asm volatile("mbarrier.arrive.relaxed.cluster.shared::cluster.b64 _, [%0];" :: "r"(mapa(bar + (B_RXFREE2 + wg) * 8, r ^ 1)) : "memory");
            uint32_t bw[2][4];
            lds128(bw[0], sb + OFF_B1 + t * 96 + 64); lds128(bw[1], sb + OFF_B1 + t * 96 + 80);
            #pragma unroll
            for (int i = 0; i < 3; i++) pre_gelu(Hb[i], acc + 32 + 8 * i, bw[i >> 1][2 * (i & 1)], bw[i >> 1][2 * (i & 1) + 1]);
            if (wg < 2) { gelu4(Hb[0]); gelu4(Hb[1]); gelu4(Hb[2]); }
            wg_wait<0>();
            features(p, phia);
            fence_async_smem();
            if (wg >= 1) {
                mbar_wait(bar + (B_RXFREE2 + wg) * 8, 0);
                const uint32_t rbar = mapa(bar + (B_RXB + wg) * 8, r ^ 1);
                #pragma unroll
                for (int i = 0; i < 3; i++) st_async4(rreg + (8 + i) * 2048, Hb[i], rbar);
            }
            mbar_wait(bar + B_KVRDY * 8, 0);
        }
        const unsigned ep = lds32(sb + OFF_EP);
        const uint32_t tag = (ep + 1) & 1;
        #define PART(o) (g_part + (size_t)((m * 8 + 2 * (o) + r) * 8 + wg * 3 + (c ^ (o)) - 1) * 512 + tw)
        #define FLAG(o) (&g_flag[m * 8 + 2 * (o) + r][wg * 3 + (c ^ (o)) - 1])
        const uint32_t xb = sb + (wg ? OFF_INC + 40960 : OFF_WBIG) + tw * 16;
        float own[32];
        {
            float o[4][12], acc[64];
            bar_sync(5 + wg, 256);
            wg_fence();
            readout_mma(o, wg);
            wg_commit();
            #pragma unroll
            for (int s = 0; s < 8; s++) {
                MMA_STAGE(3, false, if (s == 0 && k == 0) wgmma_rs128_first(acc, Ha[0], d); else if (G2_HAS(s, k)) wgmma_rs128(acc, G2_A(s, k), d));
                if (s == 0 && wg < 1) {
                    mbar_wait(bar + (B_RXFREE2 + wg) * 8, 0);
                    const uint32_t rbar = mapa(bar + (B_RXB + wg) * 8, r ^ 1);
                    #pragma unroll
                    for (int i = 0; i < 3; i++) st_async4(rreg + (8 + i) * 2048, Hb[i], rbar);
                }
                if (s == 1 || s == 2) {
                    if (s == 1) wg_wait<2>();
                    const uint32_t rbar = mapa(bar + (B_RXC + wg) * 8, r ^ 1);
                    #pragma unroll
                    for (int h = 2 * s - 2; h < 2 * s; h++) {
                        const float r0 = rcp(o[h][8] + 1e-6f), r1 = rcp(o[h][10] + 1e-6f);
                        Hb[3 + h][0] = pack2(o[h][0] * r0, o[h][1] * r0); Hb[3 + h][1] = pack2(o[h][2] * r1, o[h][3] * r1);
                        Hb[3 + h][2] = pack2(o[h][4] * r0, o[h][5] * r0); Hb[3 + h][3] = pack2(o[h][6] * r1, o[h][7] * r1);
                        st_async4(rreg + (11 + h) * 2048, Hb[3 + h], rbar);
                    }
                }
                if (s == 4) {
                    mbar_wait(bar + (B_RXB + wg) * 8, 0);
                    #pragma unroll
                    for (int i = 0; i < 3; i++) lds128(Pb[i], reg + (8 + i) * 2048 + tw * 16);
                }
                if (s == 5) {
                    mbar_wait(bar + (B_RXC + wg) * 8, 0);
                    #pragma unroll
                    for (int i = 3; i < 7; i++) lds128(Pb[i], reg + (8 + i) * 2048 + tw * 16);
                }
                if (s == 7 && wg == 0 && lane == 0) mbar_arrive(bar + B_PBDONE * 8);
                STAGE_END(false);
            }
            wg_wait<0>();
            release(sb, 7, lane);
            uint32_t pk[8][4];
            pack_tile(pk, acc, tag);
            mbar_wait(bar + (B_EMPTY + 2) * 8, 1);
            #pragma unroll
            for (int i = 0; i < 8; i++) {
                const int oc = 2 * (cc ^ 1) + (i >> 2);
                stg128(PART(oc) + (i & 3) * 128, pk[i]);
                if ((i & 3) == 3) set_flag(FLAG(oc), w, ep + 1, lane);
            }
        }
        const uint32_t tb = sb + 6 * STB + wg * 65536;
        const uint4* const mine = g_part + (size_t)((m * 8 + j) * 8 + wg * 3) * 512 + tw;
        uint32_t xv[4][4];
        #pragma unroll
        for (int hf = 0; hf < 2; hf++) {
            float oth[32];
            mbar_wait(bar + (B_FULLB + 2 * hf) * 8, 0);
            bar_sync(5 + wg, 256);
            #pragma unroll
            for (int n = 0; n < 8; n++) {
                const int s = (n & 1) | ((n & 2) << 1) | ((n & 4) >> 1);
                if (n == 4) mbar_wait(bar + (B_FULLB + 2 * hf + 1) * 8, 0);
                if (n == 0 || n == 4) wg_fence();
                #pragma unroll
                for (int k = 0; k < 4; k++) {
                    const int q = 2 * hf + ((s >> 1) & 1);
                    const uint64_t d = dB + (((q ? (2 * q - 2) * STB : OFF_INC) + (s < 4 ? (s & 1) * 8192 : (s & 1) ? 22528 : 16384) + k * 2048) >> 4);
                    if (hf == 0) { if (s == 0 && k == 0) wgmma_rs64_first(oth, Ha[0], d); else if (G2_HAS(s, k)) wgmma_rs64(oth, G2_A(s, k), d); }
                    else { if (s == 0 && k == 0) wgmma_rs64_first(own, Ha[0], d); else if (G2_HAS(s, k)) wgmma_rs64(own, G2_A(s, k), d); }
                }
                if (s == 7 && (hf & wg) == 0) bar_arrive(6 - wg, 256);
                if (s == 7) wg_commit();
            }
            if (hf == 0) {
                wg_wait<0>();
                uint32_t pk[4][4];
                pack_tile(pk, oth, tag);
                #pragma unroll
                for (int i = 0; i < 4; i++) stg128(PART(c ^ 1) + i * 128, pk[i]);
                set_flag(FLAG(c ^ 1), w, ep + 1, lane);
                mbar_wait(bar + B_XRES * 8, 0);
                uint32_t bw[2][4];
                lds128(bw[0], sb + OFF_B2 + t * 32); lds128(bw[1], sb + OFF_B2 + t * 32 + 16);
                #pragma unroll
                for (int i = 0; i < 4; i++) ldsm4(xv[i], sb + 7 * STB + wg * 8192 + lrow * 128 + (swz ^ (32 * i)));
                if (wg < 2) {
                    #pragma unroll
                    for (int i = 0; i < 16; i++) xv[i >> 2][i & 3] = add2(xv[i >> 2][i & 3], bw[i >> 3][(i >> 1) & 3]);
                }
            }
        }
        {
            uint32_t ost = tb + 8192 + wg * 16384 + w * 2048, oa = ost + (lane & 15) * 128 + swz;
            uint32_t u[8][4];
            mbar_wait(bar + (B_TILE + wg) * 8, 0);
            #pragma unroll
            for (int i = 0; i < 8; i++) lds128(u[i], xb + i * 2048);
            check_tile(u, mine + 512, tag);
            wg_wait<0>();
            if (wg < 2) {
                #pragma unroll
                for (int i = 0; i < 16; i++)
                    xv[i >> 2][i & 3] = add2(xv[i >> 2][i & 3], add2(add2(u[i >> 2][i & 3], u[4 + (i >> 2)][i & 3]), pack2(own[2 * i], own[2 * i + 1])));
            }
            uint32_t v[4][4];
            mbar_wait(bar + (B_TILE + 2 + wg) * 8, 0);
            #pragma unroll
            for (int i = 0; i < 4; i++) lds128(v[i], tb + tw * 16 + i * 2048);
            check_tile(v, mine, tag);
            if (lane == 0) mbar_arrive(bar + B_DONE * 8);
            #pragma unroll
            for (int i = 0; i < 4; i++) {
                stsm4(oa ^ (32 * i), add2(xv[i][0], v[i][0]), add2(xv[i][1], v[i][1]), add2(xv[i][2], v[i][2]), add2(xv[i][3], v[i][3]));
            }
            __syncwarp();
            uint4* op = (uint4*)P.outp + (size_t)(m * 128 + wg * 64 + 16 * w + (lane >> 3)) * 64 + (4 * r + c) * 8 + (lane & 7);
            #pragma unroll
            for (int i = 0; i < 4; i++) lds128(v[i], ((ost + (lane >> 3) * 128 + (((lane ^ (lane >> 3)) & 7) << 4)) ^ ((i & 1) * 64)) + i * 512);
            #pragma unroll
            for (int i = 0; i < 4; i++) op[i * 256] = make_uint4(v[i][0], v[i][1], v[i][2], v[i][3]);
            if (blockIdx.x == 0 && tid == 128) asm volatile("st.relaxed.gpu.global.u32 [%0], %1;" :: "l"(&g_epoch), "r"(ep + 1) : "memory");
        }
    }
}

typedef CUresult (*EncFn)(CUtensorMap*, CUtensorMapDataType, cuuint32_t, void*, const cuuint64_t*, const cuuint64_t*, const cuuint32_t*,
                          const cuuint32_t*, CUtensorMapInterleave, CUtensorMapSwizzle, CUtensorMapL2promotion, CUtensorMapFloatOOBfill);

void encode(EncFn enc, CUtensorMap* tm, const void* base, int rank, cuuint64_t d0, cuuint64_t d1, cuuint64_t d2, cuuint64_t s1, cuuint64_t s2,
            cuuint32_t b0, cuuint32_t b1, cuuint32_t b2) {
    cuuint64_t gd[3] = {d0, d1, d2}, gs[2] = {s1, s2};
    cuuint32_t bd[3] = {b0, b1, b2}, es[3] = {1, 1, 1};
    enc(tm, CU_TENSOR_MAP_DATA_TYPE_BFLOAT16, rank, const_cast<void*>(base), gd, gs, bd, es, CU_TENSOR_MAP_INTERLEAVE_NONE,
        CU_TENSOR_MAP_SWIZZLE_128B, CU_TENSOR_MAP_L2_PROMOTION_L2_128B, CU_TENSOR_MAP_FLOAT_OOB_FILL_NONE);
}

}

extern "C" void kernel_launch(void* const* d_in, const int* in_sizes, int n_in, void* d_out, int out_size) {
    (void)in_sizes; (void)n_in; (void)out_size;
    static EncFn enc = nullptr;
    if (!enc) {
        void* fn = nullptr;
        cudaDriverEntryPointQueryResult qr;
        cudaGetDriverEntryPoint("cuTensorMapEncodeTiled", &fn, cudaEnableDefault, &qr);
        enc = (EncFn)fn;
        cudaFuncSetAttribute(fused_kernel, cudaFuncAttributeMaxDynamicSharedMemorySize, SMEM_BYTES);
    }
    Params P;
    encode(enc, &P.x, d_in[0], 3, 64, 2048, 8, 1024, 128, 64, 64, 2);
    encode(enc, &P.kv, d_in[1], 3, 512, 512, 3, 3072, 1024, 64, 64, 2);
    encode(enc, &P.q, d_in[1], 3, 512, 512, 3, 3072, 1024, 64, 64, 1);
    encode(enc, &P.w1a, d_in[5], 3, 1376, 512, 2, 2752, 128, 64, 64, 2);
    encode(enc, &P.w1b, d_in[5], 3, 1376, 512, 2, 2752, 128, 64, 64, 1);
    encode(enc, &P.w2h, d_in[7], 3, 64, 1376, 8, 1024, 128, 64, 88, 1);
    encode(enc, &P.woh, d_in[3], 3, 64, 512, 8, 1024, 128, 64, 64, 1);
    encode(enc, &P.w2, d_in[7], 3, 64, 1376, 8, 1024, 128, 64, 64, 2);
    encode(enc, &P.wo, d_in[3], 3, 64, 512, 8, 1024, 128, 64, 64, 2);
    encode(enc, &P.xr, d_in[0], 3, 64, 2048, 8, 1024, 128, 64, 128, 1);
    P.outp = d_out;
    P.xp = (const __nv_bfloat16*)d_in[0];
    P.wphi = (const __nv_bfloat16*)d_in[2];
    P.b1 = (const __nv_bfloat16*)d_in[6];
    P.b2 = (const __nv_bfloat16*)d_in[8];
    fused_kernel<<<128, 384, SMEM_BYTES, cudaStreamPerThread>>>(P);
}
```

```cpp
#include <cuda_runtime.h>
#include <cuda_bf16.h>
#include <cuda.h>
#include <stdint.h>

#define REL 3
#define CWARM 1
#define PROF_P0 9
#define PROF_P1 9
namespace {

constexpr uint32_t SMEM_BASE = 1024;
constexpr int NST = 8;
constexpr int STB = 16384;
constexpr int OFF_INC = NST * STB;
constexpr int OFF_SPARE = OFF_INC + 65536;
constexpr int OFF_WBIG = OFF_SPARE + 16384;
constexpr int OFF_ONES = OFF_WBIG + 8192;
constexpr int OFF_KVB = OFF_ONES + 1024;
constexpr int OFF_B1 = OFF_KVB + 8704;
constexpr int OFF_B2 = OFF_B1 + 384;
constexpr int OFF_EP = OFF_B2 + 128;
constexpr int OFF_BAR = OFF_EP + 16;
enum { B_XFULL = 0, B_FULL = 8, B_RXA = 19, B_RXB = 21, B_RXC = 23, B_RXFREE = 25, B_MISC = 27, B_XRES = 28, B_KVRAW = 29, B_RXFREE2 = 30, B_FULLB = 32, B_TILE = 36,
       B_KVRD = 40, B_EMPTY = 42, B_DONE = 50, B_XFREE = 51, B_KVST = 53, B_PBDONE = 55, B_HAST = 56, B_KVRDY = 58, B_NUM = 59 };
constexpr int SMEM_BYTES = OFF_BAR + B_NUM * 8;
static_assert(SMEM_BYTES <= 232448, "smem");
constexpr int R_KVP = 24576;
constexpr int R_V = 16384;
constexpr int KV_FLOATS = 2176;

__device__ __align__(128) float g_kv[2][8][KV_FLOATS];
__device__ __align__(128) unsigned g_cnt[2][8][32];
__device__ unsigned g_epoch;
__device__ __align__(128) uint4 g_flag[128][8];
__device__ uint4 g_part[128 * 8 * 512];
#define TS(i)
#define TP(i)
#define TSS(p, s)
#define TSW(w, i)
#define TSDUMP()
#define TG(i)
#define LAUNCH_SMEM SMEM_BYTES

struct Params {
    CUtensorMap x, kv, q, w1a, w1b, w2, wo, xr, w2h, woh;
    const __nv_bfloat16* wphi;
    const __nv_bfloat16* b1;
    const __nv_bfloat16* b2;
    void* outp;
    const __nv_bfloat16* xp;
};

__device__ __forceinline__ void mbar_init(uint32_t bar, uint32_t cnt) { asm volatile("mbarrier.init.shared::cta.b64 [%0], %1;" :: "r"(bar), "r"(cnt) : "memory"); }
__device__ __forceinline__ void mbar_expect_tx(uint32_t bar, uint32_t bytes) { asm volatile("mbarrier.arrive.expect_tx.shared::cta.b64 _, [%0], %1;" :: "r"(bar), "r"(bytes) : "memory"); }
__device__ __forceinline__ void mbar_arrive(uint32_t bar) { asm volatile("mbarrier.arrive.shared::cta.b64 _, [%0];" :: "r"(bar) : "memory"); }
__device__ __forceinline__ void mbar_wait(uint32_t bar, uint32_t parity) {
    asm volatile("{\n"
        ".reg .pred p;\n"
        "WL%=:\n"
        "mbarrier.try_wait.parity.shared::cta.b64 p, [%0], %1;\n"
        "@!p bra WL%=;\n"
        "}" :: "r"(bar), "r"(parity) : "memory");
}
__device__ __forceinline__ void tma3d(uint32_t dst, const CUtensorMap* tm, int c0, int c1, int c2, uint32_t bar) {
    asm volatile("cp.async.bulk.tensor.3d.shared::cluster.global.mbarrier::complete_tx::bytes [%0], [%1, {%3, %4, %5}], [%2];"
        :: "r"(dst), "l"(tm), "r"(bar), "r"(c0), "r"(c1), "r"(c2) : "memory");
}
__device__ __forceinline__ void pf3d(const CUtensorMap* tm, int c0, int c1, int c2) {
    asm volatile("cp.async.bulk.prefetch.tensor.3d.L2.global [%0, {%1, %2, %3}];" :: "l"(tm), "r"(c0), "r"(c1), "r"(c2) : "memory");
}
__device__ __forceinline__ bool elect_one() {
    uint32_t p;
    asm volatile("{ .reg .pred P; elect.sync _|P, 0xffffffff; selp.u32 %0, 1, 0, P; }" : "=r"(p));
    return p;
}
__device__ __forceinline__ void wg_fence() { asm volatile("wgmma.fence.sync.aligned;" ::: "memory"); }
__device__ __forceinline__ void wg_commit() { asm volatile("wgmma.commit_group.sync.aligned;" ::: "memory"); }
template <int N> __device__ __forceinline__ void wg_wait() { asm volatile("wgmma.wait_group.sync.aligned %0;" :: "n"(N) : "memory"); }
__device__ __forceinline__ void fence_async_smem() { asm volatile("fence.proxy.async.shared::cta;" ::: "memory"); }
__device__ __forceinline__ void bar_sync(int id, int n) { asm volatile("bar.sync %0, %1;" :: "r"(id), "r"(n) : "memory"); }
__device__ __forceinline__ void bar_arrive(int id, int n) { asm volatile("bar.arrive %0, %1;" :: "r"(id), "r"(n) : "memory"); }
__device__ __forceinline__ void ldsm4(uint32_t (&r)[4], uint32_t addr) {
    asm volatile("ldmatrix.sync.aligned.m8n8.x4.shared.b16 {%0,%1,%2,%3}, [%4];" : "=r"(r[0]), "=r"(r[1]), "=r"(r[2]), "=r"(r[3]) : "r"(addr) : "memory");
}
__device__ __forceinline__ void stsm4(uint32_t addr, uint32_t a, uint32_t b, uint32_t c, uint32_t d) {
    asm volatile("stmatrix.sync.aligned.m8n8.x4.shared.b16 [%0], {%1,%2,%3,%4};" :: "r"(addr), "r"(a), "r"(b), "r"(c), "r"(d) : "memory");
}
__device__ __forceinline__ void lds128(uint32_t (&r)[4], uint32_t addr) {
    asm volatile("ld.shared.v4.b32 {%0,%1,%2,%3}, [%4];" : "=r"(r[0]), "=r"(r[1]), "=r"(r[2]), "=r"(r[3]) : "r"(addr) : "memory");
}
__device__ __forceinline__ uint32_t lds32(uint32_t addr) { uint32_t r; asm volatile("ld.shared.b32 %0, [%1];" : "=r"(r) : "r"(addr) : "memory"); return r; }
__device__ __forceinline__ void sts128(uint32_t addr, uint32_t a, uint32_t b, uint32_t c, uint32_t d) {
    asm volatile("st.shared.v4.b32 [%0], {%1,%2,%3,%4};" :: "r"(addr), "r"(a), "r"(b), "r"(c), "r"(d) : "memory");
}
__device__ __forceinline__ void sts32(uint32_t addr, uint32_t a) { asm volatile("st.shared.b32 [%0], %1;" :: "r"(addr), "r"(a) : "memory"); }
__device__ __forceinline__ void st_async4(uint32_t addr, const uint32_t (&v)[4], uint32_t bar) {
    asm volatile("st.async.weak.shared::cluster.mbarrier::complete_tx::bytes.v4.b32 [%0], {%1,%2,%3,%4}, [%5];"
        :: "r"(addr), "r"(v[0]), "r"(v[1]), "r"(v[2]), "r"(v[3]), "r"(bar) : "memory");
}
__device__ __forceinline__ uint32_t mapa(uint32_t addr, uint32_t cta) { uint32_t r; asm("mapa.shared::cluster.u32 %0, %1, %2;" : "=r"(r) : "r"(addr), "r"(cta)); return r; }
__device__ __forceinline__ void mma_ones(float (&d)[4], const uint32_t (&a)[4]) {
    asm("mma.sync.aligned.m16n8k16.row.col.f32.bf16.bf16.f32 {%0,%1,%2,%3}, {%4,%5,%6,%7}, {%8,%8}, {%0,%1,%2,%3};"
        : "+f"(d[0]), "+f"(d[1]), "+f"(d[2]), "+f"(d[3]) : "r"(a[0]), "r"(a[1]), "r"(a[2]), "r"(a[3]), "r"(0x3F803F80u));
}
__device__ __forceinline__ uint32_t add2(uint32_t a, uint32_t b) { uint32_t r; asm("add.rn.bf16x2 %0, %1, %2;" : "=r"(r) : "r"(a), "r"(b)); return r; }
__device__ __forceinline__ uint32_t pack2(float lo, float hi) { uint32_t r; asm("cvt.rn.bf16x2.f32 %0, %1, %2;" : "=r"(r) : "f"(hi), "f"(lo)); return r; }
__device__ __forceinline__ uint32_t pack2v(float lo, float hi) { uint32_t r; asm volatile("cvt.rn.bf16x2.f32 %0, %1, %2;" : "=r"(r) : "f"(hi), "f"(lo)); return r; }
__device__ __forceinline__ float bflo(uint32_t w) { return __uint_as_float(w << 16); }
__device__ __forceinline__ float bfhi(uint32_t w) { return __uint_as_float(w & 0xffff0000u); }
__device__ __forceinline__ float rcp(float x) { float r; asm("rcp.approx.ftz.f32 %0, %1;" : "=f"(r) : "f"(x)); return r; }
__device__ __forceinline__ float rsq(float x) { float r; asm("rsqrt.approx.ftz.f32 %0, %1;" : "=f"(r) : "f"(x)); return r; }
__device__ __forceinline__ uint32_t sub2(uint32_t a, uint32_t b) { uint32_t r; asm("sub.rn.bf16x2 %0, %1, %2;" : "=r"(r) : "r"(a), "r"(b)); return r; }
__device__ __forceinline__ void wgmma_rs128_first(float (&d)[64], const uint32_t (&a)[4], uint64_t db) {
    asm volatile("{ .reg .pred p; setp.ne.b32 p, 0, 0; wgmma.mma_async.sync.aligned.m64n128k16.f32.bf16.bf16 "
        "{%0,%1,%2,%3,%4,%5,%6,%7,%8,%9,%10,%11,%12,%13,%14,%15,%16,%17,%18,%19,%20,%21,%22,%23,%24,%25,%26,%27,%28,%29,%30,%31,%32,%33,%34,%35,%36,%37,%38,%39,%40,%41,%42,%43,%44,%45,%46,%47,%48,%49,%50,%51,%52,%53,%54,%55,%56,%57,%58,%59,%60,%61,%62,%63}, {%64,%65,%66,%67}, %68, p, 1, 1, 1; }"
        : "=f"(d[0]),"=f"(d[1]),"=f"(d[2]),"=f"(d[3]),"=f"(d[4]),"=f"(d[5]),"=f"(d[6]),"=f"(d[7]),"=f"(d[8]),"=f"(d[9]),"=f"(d[10]),"=f"(d[11]),"=f"(d[12]),"=f"(d[13]),"=f"(d[14]),"=f"(d[15]),"=f"(d[16]),"=f"(d[17]),"=f"(d[18]),"=f"(d[19]),"=f"(d[20]),"=f"(d[21]),"=f"(d[22]),"=f"(d[23]),"=f"(d[24]),"=f"(d[25]),"=f"(d[26]),"=f"(d[27]),"=f"(d[28]),"=f"(d[29]),"=f"(d[30]),"=f"(d[31]),"=f"(d[32]),"=f"(d[33]),"=f"(d[34]),"=f"(d[35]),"=f"(d[36]),"=f"(d[37]),"=f"(d[38]),"=f"(d[39]),"=f"(d[40]),"=f"(d[41]),"=f"(d[42]),"=f"(d[43]),"=f"(d[44]),"=f"(d[45]),"=f"(d[46]),"=f"(d[47]),"=f"(d[48]),"=f"(d[49]),"=f"(d[50]),"=f"(d[51]),"=f"(d[52]),"=f"(d[53]),"=f"(d[54]),"=f"(d[55]),"=f"(d[56]),"=f"(d[57]),"=f"(d[58]),"=f"(d[59]),"=f"(d[60]),"=f"(d[61]),"=f"(d[62]),"=f"(d[63])
        : "r"(a[0]), "r"(a[1]), "r"(a[2]), "r"(a[3]), "l"(db));
}
__device__ __forceinline__ void wgmma_rs128(float (&d)[64], const uint32_t (&a)[4], uint64_t db) {
    asm volatile("{ .reg .pred p; setp.ne.b32 p, 1, 0; wgmma.mma_async.sync.aligned.m64n128k16.f32.bf16.bf16 "
        "{%0,%1,%2,%3,%4,%5,%6,%7,%8,%9,%10,%11,%12,%13,%14,%15,%16,%17,%18,%19,%20,%21,%22,%23,%24,%25,%26,%27,%28,%29,%30,%31,%32,%33,%34,%35,%36,%37,%38,%39,%40,%41,%42,%43,%44,%45,%46,%47,%48,%49,%50,%51,%52,%53,%54,%55,%56,%57,%58,%59,%60,%61,%62,%63}, {%64,%65,%66,%67}, %68, p, 1, 1, 1; }"
        : "+f"(d[0]),"+f"(d[1]),"+f"(d[2]),"+f"(d[3]),"+f"(d[4]),"+f"(d[5]),"+f"(d[6]),"+f"(d[7]),"+f"(d[8]),"+f"(d[9]),"+f"(d[10]),"+f"(d[11]),"+f"(d[12]),"+f"(d[13]),"+f"(d[14]),"+f"(d[15]),"+f"(d[16]),"+f"(d[17]),"+f"(d[18]),"+f"(d[19]),"+f"(d[20]),"+f"(d[21]),"+f"(d[22]),"+f"(d[23]),"+f"(d[24]),"+f"(d[25]),"+f"(d[26]),"+f"(d[27]),"+f"(d[28]),"+f"(d[29]),"+f"(d[30]),"+f"(d[31]),"+f"(d[32]),"+f"(d[33]),"+f"(d[34]),"+f"(d[35]),"+f"(d[36]),"+f"(d[37]),"+f"(d[38]),"+f"(d[39]),"+f"(d[40]),"+f"(d[41]),"+f"(d[42]),"+f"(d[43]),"+f"(d[44]),"+f"(d[45]),"+f"(d[46]),"+f"(d[47]),"+f"(d[48]),"+f"(d[49]),"+f"(d[50]),"+f"(d[51]),"+f"(d[52]),"+f"(d[53]),"+f"(d[54]),"+f"(d[55]),"+f"(d[56]),"+f"(d[57]),"+f"(d[58]),"+f"(d[59]),"+f"(d[60]),"+f"(d[61]),"+f"(d[62]),"+f"(d[63])
        : "r"(a[0]), "r"(a[1]), "r"(a[2]), "r"(a[3]), "l"(db));
}
__device__ __forceinline__ void wgmma_rs112_first(float (&d)[56], const uint32_t (&a)[4], uint64_t db) {
    asm volatile("{ .reg .pred p; setp.ne.b32 p, 0, 0; wgmma.mma_async.sync.aligned.m64n112k16.f32.bf16.bf16 "
        "{%0,%1,%2,%3,%4,%5,%6,%7,%8,%9,%10,%11,%12,%13,%14,%15,%16,%17,%18,%19,%20,%21,%22,%23,%24,%25,%26,%27,%28,%29,%30,%31,%32,%33,%34,%35,%36,%37,%38,%39,%40,%41,%42,%43,%44,%45,%46,%47,%48,%49,%50,%51,%52,%53,%54,%55}, {%56,%57,%58,%59}, %60, p, 1, 1, 1; }"
        : "=f"(d[0]),"=f"(d[1]),"=f"(d[2]),"=f"(d[3]),"=f"(d[4]),"=f"(d[5]),"=f"(d[6]),"=f"(d[7]),"=f"(d[8]),"=f"(d[9]),"=f"(d[10]),"=f"(d[11]),"=f"(d[12]),"=f"(d[13]),"=f"(d[14]),"=f"(d[15]),"=f"(d[16]),"=f"(d[17]),"=f"(d[18]),"=f"(d[19]),"=f"(d[20]),"=f"(d[21]),"=f"(d[22]),"=f"(d[23]),"=f"(d[24]),"=f"(d[25]),"=f"(d[26]),"=f"(d[27]),"=f"(d[28]),"=f"(d[29]),"=f"(d[30]),"=f"(d[31]),"=f"(d[32]),"=f"(d[33]),"=f"(d[34]),"=f"(d[35]),"=f"(d[36]),"=f"(d[37]),"=f"(d[38]),"=f"(d[39]),"=f"(d[40]),"=f"(d[41]),"=f"(d[42]),"=f"(d[43]),"=f"(d[44]),"=f"(d[45]),"=f"(d[46]),"=f"(d[47]),"=f"(d[48]),"=f"(d[49]),"=f"(d[50]),"=f"(d[51]),"=f"(d[52]),"=f"(d[53]),"=f"(d[54]),"=f"(d[55])
        : "r"(a[0]), "r"(a[1]), "r"(a[2]), "r"(a[3]), "l"(db));
}
__device__ __forceinline__ void wgmma_rs112(float (&d)[56], const uint32_t (&a)[4], uint64_t db) {
    asm volatile("{ .reg .pred p; setp.ne.b32 p, 1, 0; wgmma.mma_async.sync.aligned.m64n112k16.f32.bf16.bf16 "
        "{%0,%1,%2,%3,%4,%5,%6,%7,%8,%9,%10,%11,%12,%13,%14,%15,%16,%17,%18,%19,%20,%21,%22,%23,%24,%25,%26,%27,%28,%29,%30,%31,%32,%33,%34,%35,%36,%37,%38,%39,%40,%41,%42,%43,%44,%45,%46,%47,%48,%49,%50,%51,%52,%53,%54,%55}, {%56,%57,%58,%59}, %60, p, 1, 1, 1; }"
        : "+f"(d[0]),"+f"(d[1]),"+f"(d[2]),"+f"(d[3]),"+f"(d[4]),"+f"(d[5]),"+f"(d[6]),"+f"(d[7]),"+f"(d[8]),"+f"(d[9]),"+f"(d[10]),"+f"(d[11]),"+f"(d[12]),"+f"(d[13]),"+f"(d[14]),"+f"(d[15]),"+f"(d[16]),"+f"(d[17]),"+f"(d[18]),"+f"(d[19]),"+f"(d[20]),"+f"(d[21]),"+f"(d[22]),"+f"(d[23]),"+f"(d[24]),"+f"(d[25]),"+f"(d[26]),"+f"(d[27]),"+f"(d[28]),"+f"(d[29]),"+f"(d[30]),"+f"(d[31]),"+f"(d[32]),"+f"(d[33]),"+f"(d[34]),"+f"(d[35]),"+f"(d[36]),"+f"(d[37]),"+f"(d[38]),"+f"(d[39]),"+f"(d[40]),"+f"(d[41]),"+f"(d[42]),"+f"(d[43]),"+f"(d[44]),"+f"(d[45]),"+f"(d[46]),"+f"(d[47]),"+f"(d[48]),"+f"(d[49]),"+f"(d[50]),"+f"(d[51]),"+f"(d[52]),"+f"(d[53]),"+f"(d[54]),"+f"(d[55])
        : "r"(a[0]), "r"(a[1]), "r"(a[2]), "r"(a[3]), "l"(db));
}
__device__ __forceinline__ void wgmma_rs64_first(float (&d)[32], const uint32_t (&a)[4], uint64_t db) {
    asm volatile("{ .reg .pred p; setp.ne.b32 p, 0, 0; wgmma.mma_async.sync.aligned.m64n64k16.f32.bf16.bf16 "
        "{%0,%1,%2,%3,%4,%5,%6,%7,%8,%9,%10,%11,%12,%13,%14,%15,%16,%17,%18,%19,%20,%21,%22,%23,%24,%25,%26,%27,%28,%29,%30,%31}, {%32,%33,%34,%35}, %36, p, 1, 1, 1; }"
        : "=f"(d[0]),"=f"(d[1]),"=f"(d[2]),"=f"(d[3]),"=f"(d[4]),"=f"(d[5]),"=f"(d[6]),"=f"(d[7]),"=f"(d[8]),"=f"(d[9]),"=f"(d[10]),"=f"(d[11]),"=f"(d[12]),"=f"(d[13]),"=f"(d[14]),"=f"(d[15]),"=f"(d[16]),"=f"(d[17]),"=f"(d[18]),"=f"(d[19]),"=f"(d[20]),"=f"(d[21]),"=f"(d[22]),"=f"(d[23]),"=f"(d[24]),"=f"(d[25]),"=f"(d[26]),"=f"(d[27]),"=f"(d[28]),"=f"(d[29]),"=f"(d[30]),"=f"(d[31])
        : "r"(a[0]), "r"(a[1]), "r"(a[2]), "r"(a[3]), "l"(db));
}
__device__ __forceinline__ void wgmma_rs64(float (&d)[32], const uint32_t (&a)[4], uint64_t db) {
    asm volatile("{ .reg .pred p; setp.ne.b32 p, 1, 0; wgmma.mma_async.sync.aligned.m64n64k16.f32.bf16.bf16 "
        "{%0,%1,%2,%3,%4,%5,%6,%7,%8,%9,%10,%11,%12,%13,%14,%15,%16,%17,%18,%19,%20,%21,%22,%23,%24,%25,%26,%27,%28,%29,%30,%31}, {%32,%33,%34,%35}, %36, p, 1, 1, 1; }"
        : "+f"(d[0]),"+f"(d[1]),"+f"(d[2]),"+f"(d[3]),"+f"(d[4]),"+f"(d[5]),"+f"(d[6]),"+f"(d[7]),"+f"(d[8]),"+f"(d[9]),"+f"(d[10]),"+f"(d[11]),"+f"(d[12]),"+f"(d[13]),"+f"(d[14]),"+f"(d[15]),"+f"(d[16]),"+f"(d[17]),"+f"(d[18]),"+f"(d[19]),"+f"(d[20]),"+f"(d[21]),"+f"(d[22]),"+f"(d[23]),"+f"(d[24]),"+f"(d[25]),"+f"(d[26]),"+f"(d[27]),"+f"(d[28]),"+f"(d[29]),"+f"(d[30]),"+f"(d[31])
        : "r"(a[0]), "r"(a[1]), "r"(a[2]), "r"(a[3]), "l"(db));
}
template <uint32_t AHI, uint32_t BHI>
__device__ __forceinline__ void wgmma_ss40_first(float (&d)[20], uint32_t alo, uint32_t blo) {
    asm volatile("{ .reg .pred p; .reg .b64 da, db; setp.ne.b32 p, 0, 0; mov.b64 da, {%20, %22}; mov.b64 db, {%21, %23}; "
        "wgmma.mma_async.sync.aligned.m64n40k16.f32.bf16.bf16 "
        "{%0,%1,%2,%3,%4,%5,%6,%7,%8,%9,%10,%11,%12,%13,%14,%15,%16,%17,%18,%19}, da, db, p, 1, 1, 1, 1; }"
        : "=f"(d[0]),"=f"(d[1]),"=f"(d[2]),"=f"(d[3]),"=f"(d[4]),"=f"(d[5]),"=f"(d[6]),"=f"(d[7]),"=f"(d[8]),"=f"(d[9]),"=f"(d[10]),"=f"(d[11]),"=f"(d[12]),"=f"(d[13]),"=f"(d[14]),"=f"(d[15]),"=f"(d[16]),"=f"(d[17]),"=f"(d[18]),"=f"(d[19])
        : "r"(alo), "r"(blo), "n"(AHI), "n"(BHI));
}
template <uint32_t AHI, uint32_t BHI>
__device__ __forceinline__ void wgmma_ss40(float (&d)[20], uint32_t alo, uint32_t blo) {
    asm volatile("{ .reg .pred p; .reg .b64 da, db; setp.ne.b32 p, 1, 0; mov.b64 da, {%20, %22}; mov.b64 db, {%21, %23}; "
        "wgmma.mma_async.sync.aligned.m64n40k16.f32.bf16.bf16 "
        "{%0,%1,%2,%3,%4,%5,%6,%7,%8,%9,%10,%11,%12,%13,%14,%15,%16,%17,%18,%19}, da, db, p, 1, 1, 1, 1; }"
        : "+f"(d[0]),"+f"(d[1]),"+f"(d[2]),"+f"(d[3]),"+f"(d[4]),"+f"(d[5]),"+f"(d[6]),"+f"(d[7]),"+f"(d[8]),"+f"(d[9]),"+f"(d[10]),"+f"(d[11]),"+f"(d[12]),"+f"(d[13]),"+f"(d[14]),"+f"(d[15]),"+f"(d[16]),"+f"(d[17]),"+f"(d[18]),"+f"(d[19])
        : "r"(alo), "r"(blo), "n"(AHI), "n"(BHI));
}
template <uint32_t AHI, uint32_t BHI>
__device__ __forceinline__ void wgmma_ss24_first(float (&d)[12], uint32_t alo, uint32_t blo) {
    asm volatile("{ .reg .pred p; .reg .b64 da, db; setp.ne.b32 p, 0, 0; mov.b64 da, {%12, %14}; mov.b64 db, {%13, %15}; "
        "wgmma.mma_async.sync.aligned.m64n24k16.f32.bf16.bf16 "
        "{%0,%1,%2,%3,%4,%5,%6,%7,%8,%9,%10,%11}, da, db, p, 1, 1, 0, 1; }"
        : "=f"(d[0]),"=f"(d[1]),"=f"(d[2]),"=f"(d[3]),"=f"(d[4]),"=f"(d[5]),"=f"(d[6]),"=f"(d[7]),"=f"(d[8]),"=f"(d[9]),"=f"(d[10]),"=f"(d[11])
        : "r"(alo), "r"(blo), "n"(AHI), "n"(BHI));
}
template <uint32_t AHI, uint32_t BHI>
__device__ __forceinline__ void wgmma_ss24(float (&d)[12], uint32_t alo, uint32_t blo) {
    asm volatile("{ .reg .pred p; .reg .b64 da, db; setp.ne.b32 p, 1, 0; mov.b64 da, {%12, %14}; mov.b64 db, {%13, %15}; "
        "wgmma.mma_async.sync.aligned.m64n24k16.f32.bf16.bf16 "
        "{%0,%1,%2,%3,%4,%5,%6,%7,%8,%9,%10,%11}, da, db, p, 1, 1, 0, 1; }"
        : "+f"(d[0]),"+f"(d[1]),"+f"(d[2]),"+f"(d[3]),"+f"(d[4]),"+f"(d[5]),"+f"(d[6]),"+f"(d[7]),"+f"(d[8]),"+f"(d[9]),"+f"(d[10]),"+f"(d[11])
        : "r"(alo), "r"(blo), "n"(AHI), "n"(BHI));
}

constexpr uint32_t ONES2 = 0x3F803F80u;

__device__ __forceinline__ uint32_t fma2(uint32_t a, uint32_t b, uint32_t c) { uint32_t r; asm("fma.rn.bf16x2 %0, %1, %2, %3;" : "=r"(r) : "r"(a), "r"(b), "r"(c)); return r; }
__device__ __forceinline__ uint32_t mul2(uint32_t a, uint32_t b) { uint32_t r; asm("mul.rn.bf16x2 %0, %1, %2;" : "=r"(r) : "r"(a), "r"(b)); return r; }
__device__ __forceinline__ void norm4(uint32_t (*A)[4], uint32_t s0, uint32_t s1, uint32_t o0, uint32_t o1) {
    #pragma unroll
    for (int k = 0; k < 4; k++) { A[k][0] = fma2(A[k][0], s0, o0); A[k][1] = fma2(A[k][1], s1, o1); A[k][2] = fma2(A[k][2], s0, o0); A[k][3] = fma2(A[k][3], s1, o1); }
}
__device__ __forceinline__ void stats8(const uint32_t (*A)[4], uint32_t (&o)[4]) {
    uint32_t c[8], q[4];
    #pragma unroll
    for (int i = 0; i < 8; i++) c[i] = add2(add2(A[i & 4][i & 3], A[(i & 4) + 1][i & 3]), add2(A[(i & 4) + 2][i & 3], A[(i & 4) + 3][i & 3]));
    #pragma unroll
    for (int k = 0; k < 8; k++) {
        #pragma unroll
        for (int i = 0; i < 4; i++) q[i] = k ? fma2(A[k][i], A[k][i], q[i]) : mul2(A[k][i], A[k][i]);
    }
    o[0] = add2(add2(c[0], c[4]), add2(c[2], c[6])); o[1] = add2(add2(c[1], c[5]), add2(c[3], c[7]));
    o[2] = add2(q[0], q[2]); o[3] = add2(q[1], q[3]);
}
__host__ __device__ constexpr uint64_t desc_hi(uint32_t lbo, uint32_t sbo, uint32_t swz) { return ((uint64_t)(lbo >> 4) << 16) | ((uint64_t)(sbo >> 4) << 32) | ((uint64_t)swz << 62); }

__device__ __forceinline__ void logits_issue(const float* acc, uint32_t (&a)[4][4], float (&p)[32]) {
    constexpr uint64_t dW = (uint64_t)((SMEM_BASE + OFF_WBIG) >> 4) | desc_hi(8192, 1024, 1);
    #pragma unroll
    for (int h = 0; h < 4; h++) {
        const float* k = acc + 8 * h;
        a[h][0] = pack2(k[0], k[1]); a[h][1] = pack2(k[2], k[3]); a[h][2] = pack2(k[4], k[5]); a[h][3] = pack2(k[6], k[7]);
    }
    wg_fence();
    #pragma unroll
    for (int h = 0; h < 4; h++) { if (h == 0) wgmma_rs64_first(p, a[0], dW); else wgmma_rs64(p, a[h], dW + h * 128); }
    wg_commit();
}
__device__ __forceinline__ void kv_mma(float (&kv0)[20], float (&kv1)[20], uint32_t wg) {
    constexpr uint32_t base = SMEM_BASE + OFF_INC, AHI = (uint32_t)(desc_hi(0, 1024, 1) >> 32), BHI = (uint32_t)(desc_hi(0, 512, 2) >> 32);
    const uint32_t oa = wg * 2048, ob = wg * (2048u - (2048u << 16));
    #pragma unroll
    for (int hp = 0; hp < 2; hp++) {
        #pragma unroll
        for (int ks = 0; ks < 4; ks++) {
            const uint32_t vb = base + R_V + hp * 4096 + ks * 1024;
            const uint32_t a = oa + (((base + hp * 8192 + ks * 2048) >> 4) | (512u << 16));
            const uint32_t b = ob + ((vb >> 4) | (((SMEM_BASE + OFF_ONES - vb) >> 4) << 16));
            if (hp == 0) { if (ks == 0) wgmma_ss40_first<AHI, BHI>(kv0, a, b); else wgmma_ss40<AHI, BHI>(kv0, a, b); }
            else { if (ks == 0) wgmma_ss40_first<AHI, BHI>(kv1, a, b); else wgmma_ss40<AHI, BHI>(kv1, a, b); }
        }
        wg_commit();
    }
}
__device__ __forceinline__ void readout_mma(float (&o)[4][12], uint32_t wg) {
    constexpr uint32_t base = SMEM_BASE + OFF_INC, AHI = (uint32_t)(desc_hi(0, 1024, 1) >> 32), BHI = (uint32_t)(desc_hi(0, 256, 0) >> 32);
    const uint32_t oa = wg * 2048;
    #pragma unroll
    for (int h = 0; h < 4; h++) {
        #pragma unroll
        for (int sg = 0; sg < 2; sg++) {
            const uint32_t a = oa + (((base + (h >> 1) * 8192 + 32 * ((2 * (h & 1) + sg) ^ (h >> 1))) >> 4) | (1u << 16));
            const uint32_t b = ((SMEM_BASE + OFF_KVB + h * 2048 + sg * 768) >> 4) | (8u << 16);
            if (sg == 0) wgmma_ss24_first<AHI, BHI>(o[h], a, b); else wgmma_ss24<AHI, BHI>(o[h], a, b);
        }
    }
}
__device__ __forceinline__ void features(float (&p)[32], uint32_t addr) {
    int trip = 0;
    while (true) {
        bool ok = true;
        float e[2][16], tt[2][8];
        #pragma unroll
        for (int r = 0; r < 2; r++) {
            #pragma unroll
            for (int i = 0; i < 16; i++) asm volatile("ex2.approx.ftz.f32 %0, %1;" : "=f"(e[r][i]) : "f"(p[4 * (i >> 1) + 2 * r + (i & 1)]));
            #pragma unroll
            for (int i = 0; i < 8; i++) asm volatile("ex2.approx.ftz.f32 %0, %1;" : "=f"(tt[r][i]) : "f"(-(p[4 * i + 2 * r] + p[4 * i + 2 * r + 1])));
        }
        #pragma unroll
        for (int r = 0; r < 2; r++) {
            float s[8];
            const float* t = tt[r];
            uint32_t w[8], y[8];
            #pragma unroll
            for (int i = 0; i < 8; i++) { s[i] = e[r][2 * i] + e[r][2 * i + 1]; w[i] = pack2(e[r][2 * i], e[r][2 * i + 1]); }
            const float rp = rcp(((s[0] + s[1]) + (s[2] + s[3])) + ((s[4] + s[5]) + (s[6] + s[7])));
            const float rm = rcp(fmaf(s[0], t[0], fmaf(s[1], t[1], fmaf(s[2], t[2], s[3] * t[3]))) + fmaf(s[4], t[4], fmaf(s[5], t[5], fmaf(s[6], t[6], s[7] * t[7]))));
            const uint32_t r2 = pack2(rp, rp);
            #pragma unroll
            for (int i = 0; i < 8; i += 2) {
                const uint32_t c = pack2(t[i] * rm, t[i + 1] * rm);
                asm("{ .reg .b16 l, h; .reg .b32 x, z; mov.b32 {l, h}, %4; mov.b32 x, {l, l}; mov.b32 z, {h, h}; mul.rn.bf16x2 %0, %2, x; mul.rn.bf16x2 %1, %3, z; }"
                    : "=r"(y[i]), "=r"(y[i + 1]) : "r"(w[i]), "r"(w[i + 1]), "r"(c));
            }
            sts128(addr + 1024 * r, mul2(w[0], r2), mul2(w[1], r2), mul2(w[2], r2), mul2(w[3], r2));
            sts128((addr ^ 16) + 1024 * r, mul2(w[4], r2), mul2(w[5], r2), mul2(w[6], r2), mul2(w[7], r2));
            asm volatile("{ .reg .pred k; setp.eq.b32 k, %10, 0; @k st.shared.v4.b32 [%0], {%2,%3,%4,%5}; @k st.shared.v4.b32 [%1], {%6,%7,%8,%9}; }"
                :: "r"((addr ^ 32) + 1024 * r), "r"((addr ^ 48) + 1024 * r), "r"(y[0]), "r"(y[1]), "r"(y[2]), "r"(y[3]),
                   "r"(y[4]), "r"(y[5]), "r"(y[6]), "r"(y[7]), "r"(trip) : "memory");
            ok = ok & (rp > 0x1p-40f) & (rm > 0x1p-40f);
        }
        if ((trip == 2) | ((trip == 0) & ok)) break;
        if (trip == 1) {
            #pragma unroll
            for (int i = 0; i < 32; i += 2) { const float a = p[i]; p[i] = -p[i + 1]; p[i + 1] = -a; }
            addr ^= 32;
        }
        float m0 = p[0], m1 = p[2];
        #pragma unroll
        for (int i = 0; i < 32; i++) { if (i & 2) m1 = fmaxf(m1, p[i]); else m0 = fmaxf(m0, p[i]); }
        #pragma unroll
        for (int i = 0; i < 32; i++) p[i] -= (i & 2) ? m1 : m0;
        trip++;
    }
    __syncwarp();
}
__device__ __forceinline__ uint32_t gelu2(uint32_t h) {
    uint32_t u = mul2(h, fma2(mul2(h, h), 0x3E923E92u, 0x3FCC3FCCu));
    asm("tanh.approx.bf16x2 %0, %0;" : "+r"(u));
    return fma2(h, u, h);
}
__device__ __forceinline__ void pre_gelu(uint32_t (&o)[4], const float* a, uint32_t ba, uint32_t bb) {
    o[0] = fma2(pack2v(a[0], a[1]), 0x3F003F00u, ba); o[1] = fma2(pack2v(a[2], a[3]), 0x3F003F00u, ba);
    o[2] = fma2(pack2v(a[4], a[5]), 0x3F003F00u, bb); o[3] = fma2(pack2v(a[6], a[7]), 0x3F003F00u, bb);
}
__device__ __forceinline__ void gelu4(uint32_t (&o)[4]) { o[0] = gelu2(o[0]); o[1] = gelu2(o[1]); o[2] = gelu2(o[2]); o[3] = gelu2(o[3]); }
__device__ __forceinline__ void release(uint32_t sb, int s, int lane) {
    if (lane == 0) mbar_arrive(sb + OFF_BAR + (B_EMPTY + s) * 8);
}
__device__ __forceinline__ void wait_full(uint32_t sb, int s, int pass) { mbar_wait(sb + OFF_BAR + (B_FULL + (s < 7 ? s : 7 + pass)) * 8, s < 7 ? pass & 1 : 0); }

__device__ __forceinline__ void store_kv(const float (&kv)[20], uint32_t o, uint32_t zo, bool hi, int t) {
    #pragma unroll
    for (int nt = 0; nt < 2; nt++)
        sts128(o + nt * 512, __float_as_uint(hi ? kv[8 + 4 * nt] : kv[4 * nt]), __float_as_uint(hi ? kv[9 + 4 * nt] : kv[1 + 4 * nt]),
               __float_as_uint(hi ? kv[10 + 4 * nt] : kv[2 + 4 * nt]), __float_as_uint(hi ? kv[11 + 4 * nt] : kv[3 + 4 * nt]));
    if (t == 0) { sts32(zo, __float_as_uint(kv[16])); sts32(zo + 32, __float_as_uint(kv[18])); }
}
template <int N>
__device__ __forceinline__ void pack_tile(uint32_t (&p)[N][4], const float* acc, uint32_t tag) {
    #pragma unroll
    for (int i = 0; i < N; i++) {
        asm("lop3.b32 %0, %1, %2, 1, 0xD8;" : "=r"(p[i][0]) : "r"(pack2(acc[8 * i + 0], acc[8 * i + 1])), "r"(tag));
        p[i][1] = pack2(acc[8 * i + 2], acc[8 * i + 3]);
        p[i][2] = pack2(acc[8 * i + 4], acc[8 * i + 5]);
        p[i][3] = pack2(acc[8 * i + 6], acc[8 * i + 7]);
    }
}
__device__ __forceinline__ void stg128(uint4* dst, const uint32_t (&p)[4]) {
    asm volatile("st.relaxed.gpu.global.v4.b32 [%0], {%1,%2,%3,%4};" :: "l"(dst), "r"(p[0]), "r"(p[1]), "r"(p[2]), "r"(p[3]) : "memory");
}
__device__ __forceinline__ void set_flag(uint4* flag, int w, uint32_t fv, int lane) {
    if (lane == 0) asm volatile("st.relaxed.gpu.global.u32 [%0], %1;" :: "l"((uint32_t*)flag + w), "r"(fv) : "memory");
}
template <int N>
__device__ __forceinline__ void check_tile(uint32_t (&v)[N][4], const uint4* src, uint32_t tag) {
    while (true) {
        uint32_t bad = 0;
        #pragma unroll
        for (int i = 0; i < N; i++) asm("lop3.b32 %0, %0, %1, %2, 0xF6;" : "+r"(bad) : "r"(v[i][0]), "r"(tag));
        if (!__any_sync(0xffffffffu, bad & 1)) break;
        #pragma unroll
        for (int i = 0; i < N; i++)
            asm volatile("ld.relaxed.gpu.global.v4.b32 {%0,%1,%2,%3}, [%4];" : "=r"(v[i][0]), "=r"(v[i][1]), "=r"(v[i][2]), "=r"(v[i][3]) : "l"(src + i * 128) : "memory");
    }
}

#define MMA_STAGE(PASS, SPLIT, BODY)                                                       \
    if (s == 0) wait_full(sb, 0, PASS);                                                    \
    wg_fence();                                                                            \
    _Pragma("unroll")                                                                      \
    for (int k = 0; k < 4; k++) {                                                          \
        const uint64_t d = dB + (uint64_t)(((s == 7 && ((PASS) & 1) ? OFF_SPARE : s * STB) + k * 2048) >> 4); \
        BODY;                                                                              \
        if (SPLIT && s == 0 && k == 1) wg_commit();                                        \
    }                                                                                      \
    wg_commit();                                                                           \
    if (s == 7) bar_arrive(6 - wg, 256);                    \
    if (s > 1) release(sb, s - 2, lane);                                                   \
    if (s < 7) wait_full(sb, s + 1, PASS)
#define STAGE_END(SPLIT)                                                                   \
    if (s > 0 || SPLIT) wg_wait<1>();                                                      \
    if (s == 7) release(sb, 6, lane)
#define G2_A(s, k) ((s) < 2 ? Ha[4 * ((s) & 1) + (k)] : (s) < 4 ? Pa[4 * ((s) & 1) + (k)] : (s) < 6 ? Hb[3 * ((s) & 1) + (k)] : Pb[3 * ((s) & 1) + (k)])
#define G2_HAS(s, k) ((k) < 3 || ((s) != 4 && (s) != 6))

__global__ void __cluster_dims__(2, 1, 1) __launch_bounds__(384, 1)
fused_kernel(const __grid_constant__ Params P) {
    extern __shared__ __align__(1024) uint8_t smem_raw[];
    const uint32_t sb = (uint32_t)__cvta_generic_to_shared(smem_raw);
    const int tid = threadIdx.x, warp = tid >> 5, lane = tid & 31;
    const int k0 = blockIdx.x >> 1, i7 = ((k0 - 36) * 37) >> 8;
    const int G = k0 < 4 ? 0 : k0 < 36 ? (k0 - 4) & 7 : k0 - 35 - 7 * i7, gi = k0 < 4 ? k0 : k0 < 36 ? (k0 - 4) >> 3 : i7;
    unsigned role = 16 * (G >> 1) + (k0 >= 4 && k0 < 36 ? 0 : 8) + 4 * (gi >> 1) + 2 * (G & 1) + (gi & 1);
    asm volatile("" : "+r"(role));
    const int m = (role >> 2) & 15, c = role & 3, r = blockIdx.x & 1, j = 2 * c + r, cc = c >> 1;
    if (tid < 256) TS(31);
    TG(41);
    const uint32_t bar = sb + OFF_BAR;

    if (warp >= 8) {
        asm volatile("setmaxnreg.dec.sync.aligned.u32 24;");
        if (warp == 8) {
            const bool el = elect_one();
            if (el) {
                #pragma unroll
                for (int i = 4; i < B_NUM; i++) mbar_init(bar + i * 8, i == B_MISC ? 3 : i < B_EMPTY ? 1 : i < B_XFREE ? 8 : i < B_KVRDY ? 4 : 2);
                #pragma unroll
                for (int i = B_RXA; i < B_RXFREE; i++) mbar_expect_tx(bar + i * 8, i < B_RXB ? 16384 : i < B_RXC ? 6144 : 8192);
                asm volatile("fence.mbarrier_init.release.cluster;" ::: "memory");
                TP(40);
            }
            __syncwarp();
            bar_arrive(0, 384);
            asm volatile("barrier.cluster.arrive.relaxed.aligned;" ::: "memory");
            if (el) {
                #pragma unroll 1
                for (int n = 0, s = 0, i = 0; n < 8; n++) {
                    if ((0x1B >> n) & 1) {
                        mbar_expect_tx(bar + (B_XFULL + 4 + i) * 8, STB);
                        tma3d(sb + OFF_INC + i * STB, &P.x, 0, m * 128 + 64, 2 * i, bar + (B_XFULL + 4 + i) * 8);
                        i++;
                    } else {
                        mbar_expect_tx(bar + (B_FULL + s) * 8, STB);
                        tma3d(sb + s * STB, &P.kv, 64 * j, 64 * s, 1, bar + (B_FULL + s) * 8);
                        s++;
                    }
                }
                mbar_wait(bar + B_XFREE * 8, 0);
                #pragma unroll 1
                for (int s = 4; s < 8; s++) {
                    mbar_expect_tx(bar + (B_FULL + s) * 8, STB);
                    tma3d(sb + s * STB, &P.kv, 64 * j, 64 * s, 1, bar + (B_FULL + s) * 8);
                }
                if (m < 8) pf3d(&P.w1a, 176 * j, 64 * m, 0);
                else { pf3d(&P.q, 64 * j, 64 * (m - 8), 0); pf3d(&P.w1b, 176 * j + 128, 64 * (m - 8), 0); }
                mbar_wait(bar + (B_FULL + 7) * 8, 0);
                #pragma unroll 1
                for (int n = -1; n < 7; n++) {
                    const uint32_t fb = bar + (B_FULL + (n < 0 ? 8 : n)) * 8;
                    if (n >= 0) mbar_wait(bar + (B_EMPTY + n) * 8, 0);
                    mbar_expect_tx(fb, STB);
                    tma3d(n < 0 ? sb + OFF_SPARE : sb + n * STB, &P.w1a, 176 * j, 64 * (n & 7), 0, fb);
                }
                {
                    const int s = m & 7, jj = j ^ ((s >> 1) & 1), ch = 4 * r + 2 * (m >> 3);
                    if (s == 5 || s == 7) pf3d(&P.wo, 0, 64 * jj, ch);
                    else pf3d(&P.w2, 0, 176 * jj + (s < 4 ? 64 * (s & 1) : 128), ch);
                }
                #pragma unroll 1
                for (int n = -1; n < 7; n++) {
                    const int s = n & 7;
                    const uint32_t fb = bar + (B_FULL + (n < 0 ? 9 : n)) * 8;
                    mbar_wait(bar + (B_EMPTY + s) * 8, n >= 0);
                    mbar_expect_tx(fb, STB);
                    tma3d(sb + s * STB, &P.q, 64 * j, 64 * s, 0, fb);
                    tma3d(sb + s * STB + 8192, &P.w1b, 176 * j + 128, 64 * s, 0, fb);
                }
                #pragma unroll 1
                for (int g = 0; g < 2; g++) {
                    mbar_wait(bar + (B_HAST + g) * 8, 0);
                    mbar_wait(bar + (B_RXFREE + g) * 8, 0);
                    asm volatile("cp.async.bulk.shared::cluster.shared::cta.mbarrier::complete_tx::bytes [%0], [%1], 16384, [%2];"
                        :: "r"(mapa(sb + OFF_INC + g * 32768, r ^ 1)), "r"(sb + OFF_INC + g * 32768 + 16384), "r"(mapa(bar + (B_RXA + g) * 8, r ^ 1)) : "memory");
                    if (g == 0) {
                        mbar_wait(bar + (B_EMPTY + 7) * 8, 1);
                        mbar_expect_tx(bar + (B_FULL + 10) * 8, STB);
                        tma3d(sb + OFF_SPARE, &P.wo, 0, 64 * (j ^ 1), 4 * r + 2 * (cc ^ 1), bar + (B_FULL + 10) * 8);
                    }
                }
                #pragma unroll 1
                for (int s = 0; s < 8; s += 2) {
                    const int jj = j ^ ((s >> 1) & 1), ch = 4 * r + 2 * (cc ^ 1);
                    const uint32_t fb = bar + (B_FULL + s) * 8;
                    mbar_wait(bar + (B_EMPTY + s) * 8, 0);
                    mbar_expect_tx(fb, STB);
                    tma3d(sb + s * STB, &P.w2, 0, 176 * jj + 32 * (s & 4), ch, fb);
                    mbar_wait(bar + (B_EMPTY + s + 1) * 8, 0);
                    if (s < 6) {
                        mbar_expect_tx(fb + 8, STB);
                        tma3d(sb + (s + 1) * STB, s < 4 ? &P.w2 : &P.wo, 0, s < 4 ? 176 * jj + 64 : 64 * jj, ch, fb + 8);
                    }
                }
                mbar_expect_tx(bar + B_XRES * 8, STB);
                tma3d(sb + 7 * STB, &P.xr, 0, m * 128, 4 * r + c, bar + B_XRES * 8);
                #pragma unroll 1
                for (int q = 0; q < 4; q++) {
                    const int jj = j ^ (q & 1), ch = 4 * r + (c ^ (q >> 1) ^ 1);
                    const uint32_t dst = q ? sb + (2 * q - 2) * STB : sb + OFF_INC, fb = bar + (B_FULLB + q) * 8;
                    if (q) mbar_wait(bar + (B_EMPTY + 2 * q - 2) * 8, 1); else mbar_wait(bar + B_PBDONE * 8, 0);
                    mbar_expect_tx(fb, 30720);
                    tma3d(dst, &P.w2h, 0, 176 * jj, ch, fb);
                    if (q) mbar_wait(bar + (B_EMPTY + 2 * q - 1) * 8, 1);
                    tma3d(dst + 11264, &P.w2h, 0, 176 * jj + 88, ch, fb);
                    tma3d(dst + 22528, &P.woh, 0, 64 * jj, ch, fb);
                }
            }
        } else if (warp == 11) {
            asm volatile("barrier.cluster.arrive.relaxed.aligned;" ::: "memory");
            if (lane == 0) asm volatile("prefetch.tensormap [%0];" :: "l"(&P.kv) : "memory");
            bar_sync(0, 384);
            if (lane < 8) {
                const CUtensorMap* tm = &P.q + lane;
                asm volatile("prefetch.tensormap [%0];" :: "l"(tm) : "memory");
            }
            if ((sb & 0x3FFFF) != SMEM_BASE) __trap();
            sts128(sb + OFF_ONES + lane * 16, ONES2, ONES2, ONES2, ONES2);
            sts128(sb + OFF_ONES + 512 + lane * 16, ONES2, ONES2, ONES2, ONES2);
            uint32_t bv[3];
            #pragma unroll
            for (int u = 0; u < 3; u++) bv[u] = (lane + 32 * u < 88 && 88 * j + lane + 32 * u < 688) ? __ldg((const uint32_t*)P.b1 + 88 * j + lane + 32 * u) : 0u;
            const uint32_t b2v = __ldg((const uint32_t*)(P.b2 + 256 * r + 64 * c) + lane);
            #pragma unroll
            for (int u = 0; u < 3; u++) {
                const int idx = lane + 32 * u;
                if (idx < 88) sts32(sb + OFF_B1 + (idx & 3) * 96 + (idx >> 2) * 4, mul2(bv[u], 0x3F003F00u));
            }
            sts32(sb + OFF_B2 + (lane & 3) * 32 + (lane >> 2) * 4, b2v);
            fence_async_smem();
            __syncwarp();
            if (lane == 0) {
                mbar_arrive(bar + B_MISC * 8);
            }
            if (lane == 0) {
                unsigned long long t0, t1;
                asm volatile("mov.u64 %0, %globaltimer;" : "=l"(t0));
                while (true) {
                    uint32_t ok;
                    asm volatile("{ .reg .pred p; mbarrier.try_wait.parity.shared::cta.b64 p, [%1], 0, 1000000; selp.u32 %0, 1, 0, p; }" : "=r"(ok) : "r"(bar + B_DONE * 8) : "memory");
                    if (ok) break;
                    asm volatile("mov.u64 %0, %globaltimer;" : "=l"(t1));
                    if (t1 - t0 > 2000000000ull) __trap();
                }
            }
        } else {
            const int g = warp - 9;
            asm volatile("barrier.cluster.arrive.relaxed.aligned;" ::: "memory");
            bar_sync(0, 384);
            unsigned ep;
            asm volatile("ld.relaxed.gpu.global.u32 %0, [%1];" : "=r"(ep) : "l"(&g_epoch) : "memory");
            {
                uint32_t v[8];
                #pragma unroll
                for (int u = 0; u < 8; u++) asm volatile("ld.global.nc.u32 %0, [%1];" : "=r"(v[u]) : "l"((const uint32_t*)P.wphi + j * 512 + g * 256 + u * 32 + lane) : "memory");
                #pragma unroll
                for (int u = 0; u < 8; u++) {
                    const int row = u * 4 + (lane >> 3);
                    const uint32_t wv = pack2(bflo(v[u]) * 1.4426950408889634f, bfhi(v[u]) * 1.4426950408889634f);
                    const uint32_t lo = g ? 0u : wv, hi = g ? wv : 0u;
                    sts128(sb + OFF_WBIG + g * 4096 + row * 128 + (((lane ^ row) & 7) << 4), u < 4 ? lo : 0u, u < 4 ? 0u : lo, u < 4 ? hi : 0u, u < 4 ? 0u : hi);
                }
                fence_async_smem();
                __syncwarp();
                if (lane == 0) mbar_arrive(bar + B_MISC * 8);
            }
            const float* kvg = g_kv[ep & 1][j];
            unsigned* cnt = &g_cnt[ep & 1][j][0];
            {
                float4* z = (float4*)&g_kv[(ep + 1) & 1][j][m * 136];
                if (lane < 18 - 2 * g) z[g * 18 + lane] = make_float4(0.f, 0.f, 0.f, 0.f);
                if (m == 0 && lane < 8) g_cnt[(ep + 1) & 1][j][lane] = 0;
            }
            asm volatile("barrier.cluster.wait.acquire.aligned;" ::: "memory");
            if (lane == 0) {
                sts32(sb + OFF_EP, ep);
                mbar_wait(bar + (B_KVST + g) * 8, 0);
                TSW(1 + g, 4);
                asm volatile("cp.reduce.async.bulk.global.shared::cta.bulk_group.add.f32 [%0], [%1], 8192;"
                    :: "l"(kvg), "r"(sb + OFF_INC + g * 32768 + R_KVP) : "memory");
                asm volatile("cp.reduce.async.bulk.global.shared::cta.bulk_group.add.f32 [%0], [%1], 512;"
                    :: "l"(kvg + 2048), "r"(sb + OFF_KVB + g * 512) : "memory");
                asm volatile("cp.async.bulk.commit_group;" ::: "memory");
                asm volatile("cp.async.bulk.wait_group.read 0;" ::: "memory");
                mbar_arrive(bar + (B_KVRD + g) * 8);
                asm volatile("mbarrier.arrive.relaxed.cluster.shared::cluster.b64 _, [%0];" :: "r"(mapa(bar + (B_RXFREE + g) * 8, r ^ 1)) : "memory");
                asm volatile("cp.async.bulk.wait_group 0;" ::: "memory");
                TSW(1 + g, 0);
                if (REL & 1) asm volatile("fence.proxy.async.global;" ::: "memory");
                if (REL & 2) asm volatile("red.release.gpu.global.add.u32 [%0], 1;" :: "l"(cnt) : "memory");
                else asm volatile("red.relaxed.gpu.global.add.u32 [%0], 1;" :: "l"(cnt) : "memory");
                TSW(1 + g, 5);
                if (g == 1) {
                    unsigned v;
                    do { asm volatile("ld.relaxed.gpu.global.u32 %0, [%1];" : "=r"(v) : "l"(cnt) : "memory"); } while (v < 32);
                    if (REL & 4) asm volatile("fence.acq_rel.gpu;" ::: "memory");
                    TSW(1 + g, 1);
                    asm volatile("fence.proxy.async.global;" ::: "memory");
                    mbar_expect_tx(bar + B_KVRAW * 8, KV_FLOATS * 4);
                    asm volatile("cp.async.bulk.shared::cluster.global.mbarrier::complete_tx::bytes [%0], [%1], %2, [%3];"
                        :: "r"(sb + OFF_KVB), "l"(kvg), "r"(KV_FLOATS * 4), "r"(bar + B_KVRAW * 8) : "memory");
                }
            }
            __syncwarp();
            {
                uint32_t kb = sb + OFF_KVB + g * 4096 + lane * 16, zs = sb + OFF_KVB + 8192 + g * 256 + lane * 4;
                #pragma unroll 1
                for (int h = -CWARM; h < 2; h++) {
                    if (h == 0) { mbar_wait(bar + B_KVRAW * 8, 0); TSW(1 + g, 3); }
                    uint32_t w[8];
                    #pragma unroll
                    for (int u = 0; u < 4; u += 2) {
                        uint32_t v[4], y[4];
                        lds128(v, kb + u * 512); lds128(y, kb + u * 512 + 512);
                        w[2 * u] = pack2v(__uint_as_float(v[0]), __uint_as_float(v[1])); w[2 * u + 1] = pack2v(__uint_as_float(v[2]), __uint_as_float(v[3]));
                        w[2 * u + 2] = pack2v(__uint_as_float(y[0]), __uint_as_float(y[1])); w[2 * u + 3] = pack2v(__uint_as_float(y[2]), __uint_as_float(y[3]));
                    }
                    const float z = __uint_as_float(lds32(zs));
                    const uint32_t zw = pack2(z, z);
                    __syncwarp();
                    if (h >= 0) {
                        stsm4(kb, w[0], w[1], w[2], w[3]);
                        stsm4(kb + 768, w[4], w[5], w[6], w[7]);
                        sts128(kb + 512 + (lane >> 4) * 512, zw, zw, zw, zw);
                        kb += 2048; zs += 128;
                    }
                }
            }
            fence_async_smem();
            __syncwarp();
            if (lane == 0) mbar_arrive(bar + B_KVRDY * 8);
            TSW(1 + g, 2);
            const uint32_t* fp = (const uint32_t*)&g_flag[m * 8 + j][g * 3] + (lane < 12 ? lane : 0);
            const uint32_t xb = sb + (g ? OFF_INC + 40960 : OFF_WBIG);
            int state = 1;
            while (true) {
                uint32_t f;
                asm volatile("ld.relaxed.gpu.global.u32 %0, [%1];" : "=r"(f) : "l"(fp) : "memory");
                const uint32_t missing = __ballot_sync(0xffffffffu, f != ep + 1);
                #pragma unroll 1
                for (int late = 1; late >= 0; late--) {
                    if ((missing & (late ? 0xF : 0xFF0)) || (state & (2 << late))) continue;
                    state |= 2 << late;
                    if (!late) { const unsigned t0 = clock(); while ((unsigned)clock() - t0 < 200) {} }
                    if (lane == 0) TP(32 + 2 * late + g);
                    mbar_wait(bar + B_PBDONE * 8, 0);
                    mbar_wait(bar + (B_EMPTY + ((late | g) ? 6 : 0)) * 8, 1);
                    if (elect_one()) {
                        const uint32_t bytes = late ? 8192 : 16384, tbar = bar + (B_TILE + 2 * late + g) * 8;
                        mbar_expect_tx(tbar, bytes);
                        asm volatile("cp.async.bulk.shared::cluster.global.mbarrier::complete_tx::bytes [%0], [%1], %2, [%3];"
                            :: "r"(late ? sb + 6 * STB + g * 65536 : xb), "l"(g_part + (size_t)((m * 8 + j) * 8 + g * 3 + 1 - late) * 512), "r"(bytes), "r"(tbar) : "memory");
                    }
                    __syncwarp();
                }
                if (state == 7) break;
                mbar_wait(bar + B_PBDONE * 8, 0);
            }
        }
    } else {
        const bool el0 = elect_one();
        if (warp == 1 || warp == 2) asm volatile("prefetch.global.L2 [%0];" :: "l"(P.xp + (m * 128 + 8 * j) * 512 + (tid - 32) * 64) : "memory");
        if (el0 && warp == 0) {
            #pragma unroll
            for (int i = 0; i < 4; i++) mbar_init(bar + (B_XFULL + i) * 8, 1);
            asm volatile("fence.mbarrier_init.release.cluster;" ::: "memory");
            #pragma unroll
            for (int i = 0; i < 4; i++) {
                mbar_expect_tx(bar + (B_XFULL + i) * 8, STB);
                tma3d(sb + (4 + i) * STB, &P.x, 0, m * 128, 2 * i, bar + (B_XFULL + i) * 8);
            }
            TP(43);
        }
        __syncwarp();
        asm volatile("barrier.cluster.arrive.relaxed.aligned;" ::: "memory");
        asm volatile("setmaxnreg.inc.sync.aligned.u32 240;");
        bar_sync(0, 384);
        const int wg = __shfl_sync(0xffffffffu, warp >> 2, 0), w = warp & 3, t = lane & 3, g = lane >> 2, tw = tid & 127;
        const uint32_t reg = sb + OFF_INC + wg * 32768;
        const int lrow = 16 * w + (lane & 15);
        const uint32_t swz = ((lane >> 4) ^ (lane & 7)) << 4;
        const uint32_t phia = reg + (t >> 1) * 8192 + (16 * w + g) * 128 + (((4 * (t & 1)) ^ (t & 2) ^ g) << 4);
        constexpr uint64_t dB = (uint64_t)(SMEM_BASE >> 4) | desc_hi(8192, 1024, 1);

        uint32_t A[32][4];
        {
            const uint32_t xst = sb + (wg ? OFF_INC : 4 * STB) + lrow * 128;
            #define LOADX(b, i) do { mbar_wait(bar + (B_XFULL + (b) + (i)) * 8, 0); \
                _Pragma("unroll") for (int k = 8 * (i); k < 8 * (i) + 8; k++) ldsm4(A[k], xst + (k >> 2) * 8192 + (swz ^ (32 * (k & 3)))); } while (0)
            uint32_t sc0, sc1, of0, of1;
            float base0 = 0.f, base1 = 0.f;
            bool centred = false;
            while (true) {
                float st[4];
                if (wg == 0) {
                    float s4[4][4], q4[4];
                    #pragma unroll
                    for (int i = 0; i < 4; i++) { s4[0][i] = 0.f; s4[1][i] = 0.f; s4[2][i] = 0.f; s4[3][i] = 0.f; q4[i] = 0.f; }
                    LOADX(0, 0);
                    #pragma unroll
                    for (int i = 0; i < 4; i++) {
                        if (i < 3) LOADX(0, i + 1);
                        uint32_t c[4];
                        #pragma unroll
                        for (int k = 8 * i; k < 8 * i + 8; k++) {
                            mma_ones(s4[k & 3], A[k]);
                            #pragma unroll
                            for (int e = 0; e < 4; e++) c[e] = (k & 7) ? fma2(A[k][e], A[k][e], c[e]) : mul2(A[k][e], A[k][e]);
                        }
                        mma_ones(q4, c);
                    }
                    st[0] = (s4[0][0] + s4[1][0]) + (s4[2][0] + s4[3][0]); st[1] = (s4[0][2] + s4[1][2]) + (s4[2][2] + s4[3][2]); st[2] = q4[0]; st[3] = q4[2];
                } else {
                    uint32_t ps[4][4];
                    LOADX(4, 0); LOADX(4, 1); LOADX(4, 2); LOADX(4, 3);
                    #pragma unroll
                    for (int i = 0; i < 4; i++) stats8(A + 8 * i, ps[i]);
                    #pragma unroll
                    for (int i = 0; i < 4; i++) {
                        const uint32_t y = add2(ps[0][i], ps[1][i]), z = add2(ps[2][i], ps[3][i]);
                        st[i] = (bflo(y) + bfhi(y)) + (bflo(z) + bfhi(z));
                    }
                    #pragma unroll
                    for (int o = 1; o <= 2; o <<= 1) {
                        #pragma unroll
                        for (int i = 0; i < 4; i++) st[i] += __shfl_xor_sync(0xffffffffu, st[i], o);
                    }
                }
                const float mean0 = st[0] * (1.f / 512.f), mean1 = st[1] * (1.f / 512.f), q0 = st[2] * (1.f / 512.f), q1 = st[3] * (1.f / 512.f);
                const float var0 = fmaf(-mean0, mean0, q0), var1 = fmaf(-mean1, mean1, q1);
                const float rs0 = rsq(fmaxf(var0, 0.f) + 1e-5f), rs1 = rsq(fmaxf(var1, 0.f) + 1e-5f);
                const uint32_t mb = pack2(base0 + mean0, base1 + mean1);
                sc0 = pack2(rs0, rs0); sc1 = pack2(rs1, rs1);
                const float d0 = (base0 - bflo(mb)) * bflo(sc0), d1 = (base1 - bfhi(mb)) * bflo(sc1);
                of0 = pack2(d0, d0); of1 = pack2(d1, d1);
                if (centred || !__any_sync(0xffffffffu, !(var0 >= 0.5f * q0) || !(var1 >= 0.5f * q1))) break;
                base0 = bflo(mb); base1 = bfhi(mb);
                const uint32_t m0 = pack2(base0, base0), m1 = pack2(base1, base1);
                #pragma unroll 1
                for (int k = 0; k < 32; k++) {
                    const uint32_t a = xst + (k >> 2) * 8192 + (swz ^ (32 * (k & 3)));
                    uint32_t v[4];
                    ldsm4(v, a);
                    stsm4(a, sub2(v[0], m0), sub2(v[1], m1), sub2(v[2], m0), sub2(v[3], m1));
                }
                fence_async_smem();
                __syncwarp();
                centred = true;
            }
            if (lane == 0) mbar_arrive(bar + (B_XFREE + wg) * 8);
            TS(0);
            norm4(A, sc0, sc1, of0, of1);
            if (wg == 1) bar_sync(6, 256);
            float acc[64];
            #pragma unroll
            for (int s = 0; s < 8; s++) {
                MMA_STAGE(0, true, if (s == 0 && k == 0) wgmma_rs128_first(acc, A[0], d); else wgmma_rs128(acc, A[4 * s + k], d));
                if (s == 0) TS(1);
                TSS(0, s);
                if (s < 7) norm4(A + 4 * s + 4, sc0, sc1, of0, of1);
                STAGE_END(true);
            }
            mbar_wait(bar + B_MISC * 8, 0);
            wg_wait<0>();
            release(sb, 7, lane);
            TS(2);

            float p[32];
            uint32_t ka[4][4];
            logits_issue(acc, ka, p);
            mbar_wait(bar + (B_XFREE + 1) * 8, 0);
            {
                const uint32_t va = reg + R_V + lrow * 64 + (((lane >> 4) ^ ((lane >> 1) & 3)) << 4);
                #pragma unroll
                for (int h = 0; h < 4; h++) {
                    const float* v = acc + 32 + 8 * h;
                    stsm4((va ^ (32 * (h & 1))) + (h >> 1) * 4096, pack2v(v[0], v[1]), pack2v(v[2], v[3]), pack2v(v[4], v[5]), pack2v(v[6], v[7]));
                }
            }
            wg_wait<0>();
            TS(19);
            features(p, phia);
            TS(3);
            fence_async_smem();
            bar_sync(1 + wg, 128);
            float kv0[20], kv1[20];
            wg_fence();
            kv_mma(kv0, kv1, wg);
            const uint32_t kvo = reg + R_KVP + lane * 16, zo = sb + OFF_KVB + wg * 512 + (w * 16 + g) * 4;
            wg_wait<1>();
            store_kv(kv0, kvo + w * 1024, zo, w >> 1, t);
            wg_wait<0>();
            store_kv(kv1, kvo + 4096 + (w ^ 1) * 1024, (zo ^ 64) + 256, w >> 1, t);
            fence_async_smem();
            __syncwarp();
            if (lane == 0) mbar_arrive(bar + (B_KVST + wg) * 8);
            TS(4);
        }
        const uint32_t rreg = mapa(reg + tw * 16, r ^ 1);
        uint32_t Ha[8][4];
        {
            float acc[64];
            bar_sync(5 + wg, 256);
            #pragma unroll
            for (int s = 0; s < 8; s++) {
                MMA_STAGE(1, true, if (s == 0 && k == 0) wgmma_rs128_first(acc, A[0], d); else wgmma_rs128(acc, A[4 * s + k], d));
                if (s == 0) TS(20);
                TSS(1, s);
                STAGE_END(true);
            }
            mbar_wait(bar + (B_KVRD + wg) * 8, 0);
            uint32_t bw[4][4];
            #pragma unroll
            for (int i = 0; i < 4; i++) lds128(bw[i], sb + OFF_B1 + t * 96 + i * 16);
            wg_wait<0>();
            release(sb, 7, lane);
            TS(5);
            #pragma unroll
            for (int i = 7; i >= 0; i--) {
                pre_gelu(Ha[i], acc + 8 * i, bw[i >> 1][2 * (i & 1)], bw[i >> 1][2 * (i & 1) + 1]);
                gelu4(Ha[i]);
                sts128(reg + tw * 16 + (8 + i) * 2048, Ha[i][0], Ha[i][1], Ha[i][2], Ha[i][3]);
            }
            fence_async_smem();
            __syncwarp();
            if (lane == 0) mbar_arrive(bar + (B_HAST + wg) * 8);
        }
        TS(6);
        uint32_t Hb[7][4];
        uint32_t Pa[8][4], Pb[7][4];
        {
            float acc[56];
            bar_sync(5 + wg, 256);
            #pragma unroll
            for (int s = 0; s < 8; s++) {
                MMA_STAGE(2, true, if (s == 0 && k == 0) wgmma_rs112_first(acc, A[0], d); else wgmma_rs112(acc, A[4 * s + k], d));
                if (s == 0) TS(21);
                TSS(2, s);
                if (s >= 2 && s < 6) { lds128(Ha[2 * s - 4], reg + tw * 16 + (2 * s + 4) * 2048); lds128(Ha[2 * s - 3], reg + tw * 16 + (2 * s + 5) * 2048); }
                if (s == 6) mbar_wait(bar + (B_RXA + wg) * 8, 0);
                if (s >= 6) {
                    #pragma unroll
                    for (int i = 4 * s - 24; i < 4 * s - 20; i++) lds128(Pa[i], reg + i * 2048 + tw * 16);
                }
                STAGE_END(true);
            }
            wg_wait<0>();
            release(sb, 7, lane);
            TS(7);
            float p[32];
            uint32_t qa[4][4];
            logits_issue(acc, qa, p);
            bar_sync(1 + wg, 128);
            if (tw == 0) asm volatile("mbarrier.arrive.relaxed.cluster.shared::cluster.b64 _, [%0];" :: "r"(mapa(bar + (B_RXFREE2 + wg) * 8, r ^ 1)) : "memory");
            uint32_t bw[2][4];
            lds128(bw[0], sb + OFF_B1 + t * 96 + 64); lds128(bw[1], sb + OFF_B1 + t * 96 + 80);
            #pragma unroll
            for (int i = 0; i < 3; i++) pre_gelu(Hb[i], acc + 32 + 8 * i, bw[i >> 1][2 * (i & 1)], bw[i >> 1][2 * (i & 1) + 1]);
            if (wg < 2) { gelu4(Hb[0]); gelu4(Hb[1]); gelu4(Hb[2]); }
            wg_wait<0>();
            TS(17);
            features(p, phia);
            TS(8);
            fence_async_smem();
            if (wg >= 1) {
                mbar_wait(bar + (B_RXFREE2 + wg) * 8, 0);
                const uint32_t rbar = mapa(bar + (B_RXB + wg) * 8, r ^ 1);
                #pragma unroll
                for (int i = 0; i < 3; i++) st_async4(rreg + (8 + i) * 2048, Hb[i], rbar);
            }
            mbar_wait(bar + B_KVRDY * 8, 0);
            TS(9);
        }
        const unsigned ep = lds32(sb + OFF_EP);
        const uint32_t tag = (ep + 1) & 1;
        #define PART(o) (g_part + (size_t)((m * 8 + 2 * (o) + r) * 8 + wg * 3 + (c ^ (o)) - 1) * 512 + tw)
        #define FLAG(o) (&g_flag[m * 8 + 2 * (o) + r][wg * 3 + (c ^ (o)) - 1])
        const uint32_t xb = sb + (wg ? OFF_INC + 40960 : OFF_WBIG) + tw * 16;
        float own[32];
        {
            float o[4][12], acc[64];
            bar_sync(5 + wg, 256);
            wg_fence();
            readout_mma(o, wg);
            wg_commit();
            #pragma unroll
            for (int s = 0; s < 8; s++) {
                MMA_STAGE(3, false, if (s == 0 && k == 0) wgmma_rs128_first(acc, Ha[0], d); else if (G2_HAS(s, k)) wgmma_rs128(acc, G2_A(s, k), d));
                if (s == 0) TS(22);
                TSS(3, s);
                if (s == 0 && wg < 1) {
                    mbar_wait(bar + (B_RXFREE2 + wg) * 8, 0);
                    const uint32_t rbar = mapa(bar + (B_RXB + wg) * 8, r ^ 1);
                    #pragma unroll
                    for (int i = 0; i < 3; i++) st_async4(rreg + (8 + i) * 2048, Hb[i], rbar);
                }
                if (s == 1 || s == 2) {
                    if (s == 1) wg_wait<2>();
                    const uint32_t rbar = mapa(bar + (B_RXC + wg) * 8, r ^ 1);
                    #pragma unroll
                    for (int h = 2 * s - 2; h < 2 * s; h++) {
                        const float r0 = rcp(o[h][8] + 1e-6f), r1 = rcp(o[h][10] + 1e-6f);
                        Hb[3 + h][0] = pack2(o[h][0] * r0, o[h][1] * r0); Hb[3 + h][1] = pack2(o[h][2] * r1, o[h][3] * r1);
                        Hb[3 + h][2] = pack2(o[h][4] * r0, o[h][5] * r0); Hb[3 + h][3] = pack2(o[h][6] * r1, o[h][7] * r1);
                        st_async4(rreg + (11 + h) * 2048, Hb[3 + h], rbar);
                    }
                    TS(10);
                }
                if (s == 4) {
                    mbar_wait(bar + (B_RXB + wg) * 8, 0);
                    #pragma unroll
                    for (int i = 0; i < 3; i++) lds128(Pb[i], reg + (8 + i) * 2048 + tw * 16);
                }
                if (s == 5) {
                    mbar_wait(bar + (B_RXC + wg) * 8, 0);
                    #pragma unroll
                    for (int i = 3; i < 7; i++) lds128(Pb[i], reg + (8 + i) * 2048 + tw * 16);
                }
                if (s == 7 && wg == 0 && lane == 0) mbar_arrive(bar + B_PBDONE * 8);
                STAGE_END(false);
            }
            wg_wait<0>();
            release(sb, 7, lane);
            TS(11);
            uint32_t pk[8][4];
            pack_tile(pk, acc, tag);
            mbar_wait(bar + (B_EMPTY + 2) * 8, 1);
            #pragma unroll
            for (int i = 0; i < 8; i++) {
                const int oc = 2 * (cc ^ 1) + (i >> 2);
                stg128(PART(oc) + (i & 3) * 128, pk[i]);
                if ((i & 3) == 3) set_flag(FLAG(oc), w, ep + 1, lane);
            }
            TS(12);
        }
        const uint32_t tb = sb + 6 * STB + wg * 65536;
        const uint4* const mine = g_part + (size_t)((m * 8 + j) * 8 + wg * 3) * 512 + tw;
        uint32_t xv[4][4];
        #pragma unroll
        for (int hf = 0; hf < 2; hf++) {
            float oth[32];
            mbar_wait(bar + (B_FULLB + 2 * hf) * 8, 0);
            bar_sync(5 + wg, 256);
            #pragma unroll
            for (int n = 0; n < 8; n++) {
                const int s = (n & 1) | ((n & 2) << 1) | ((n & 4) >> 1);
                if (n == 4) mbar_wait(bar + (B_FULLB + 2 * hf + 1) * 8, 0);
                if (n == 0 || n == 4) wg_fence();
                #pragma unroll
                for (int k = 0; k < 4; k++) {
                    const int q = 2 * hf + ((s >> 1) & 1);
                    const uint64_t d = dB + (((q ? (2 * q - 2) * STB : OFF_INC) + (s < 4 ? (s & 1) * 8192 : (s & 1) ? 22528 : 16384) + k * 2048) >> 4);
                    if (hf == 0) { if (s == 0 && k == 0) wgmma_rs64_first(oth, Ha[0], d); else if (G2_HAS(s, k)) wgmma_rs64(oth, G2_A(s, k), d); }
                    else { if (s == 0 && k == 0) wgmma_rs64_first(own, Ha[0], d); else if (G2_HAS(s, k)) wgmma_rs64(own, G2_A(s, k), d); }
                }
                if (s == 0) TS(hf ? 27 : 23);
                TSS(4 + hf, s);
                if (s == 7 && (hf & wg) == 0) bar_arrive(6 - wg, 256);
                if (s == 7) wg_commit();
            }
            if (hf == 0) {
                wg_wait<0>();
                TS(13);
                uint32_t pk[4][4];
                pack_tile(pk, oth, tag);
                #pragma unroll
                for (int i = 0; i < 4; i++) stg128(PART(c ^ 1) + i * 128, pk[i]);
                set_flag(FLAG(c ^ 1), w, ep + 1, lane);
                TS(30);
                mbar_wait(bar + B_XRES * 8, 0);
                uint32_t bw[2][4];
                lds128(bw[0], sb + OFF_B2 + t * 32); lds128(bw[1], sb + OFF_B2 + t * 32 + 16);
                #pragma unroll
                for (int i = 0; i < 4; i++) ldsm4(xv[i], sb + 7 * STB + wg * 8192 + lrow * 128 + (swz ^ (32 * i)));
                if (wg < 2) {
                    #pragma unroll
                    for (int i = 0; i < 16; i++) xv[i >> 2][i & 3] = add2(xv[i >> 2][i & 3], bw[i >> 3][(i >> 1) & 3]);
                }
            }
        }
        {
            uint32_t ost = tb + 8192 + wg * 16384 + w * 2048, oa = ost + (lane & 15) * 128 + swz;
            uint32_t u[8][4];
            mbar_wait(bar + (B_TILE + wg) * 8, 0);
            #pragma unroll
            for (int i = 0; i < 8; i++) lds128(u[i], xb + i * 2048);
            check_tile(u, mine + 512, tag);
            wg_wait<0>();
            if (wg < 2) {
                #pragma unroll
                for (int i = 0; i < 16; i++)
                    xv[i >> 2][i & 3] = add2(xv[i >> 2][i & 3], add2(add2(u[i >> 2][i & 3], u[4 + (i >> 2)][i & 3]), pack2(own[2 * i], own[2 * i + 1])));
            }
            TS(18);
            uint32_t v[4][4];
            mbar_wait(bar + (B_TILE + 2 + wg) * 8, 0);
            #pragma unroll
            for (int i = 0; i < 4; i++) lds128(v[i], tb + tw * 16 + i * 2048);
            check_tile(v, mine, tag);
            if (lane == 0) mbar_arrive(bar + B_DONE * 8);
            TS(14);
            #pragma unroll
            for (int i = 0; i < 4; i++) {
                stsm4(oa ^ (32 * i), add2(xv[i][0], v[i][0]), add2(xv[i][1], v[i][1]), add2(xv[i][2], v[i][2]), add2(xv[i][3], v[i][3]));
            }
            TS(28);
            __syncwarp();
            uint4* op = (uint4*)P.outp + (size_t)(m * 128 + wg * 64 + 16 * w + (lane >> 3)) * 64 + (4 * r + c) * 8 + (lane & 7);
            #pragma unroll
            for (int i = 0; i < 4; i++) lds128(v[i], ((ost + (lane >> 3) * 128 + (((lane ^ (lane >> 3)) & 7) << 4)) ^ ((i & 1) * 64)) + i * 512);
            #pragma unroll
            for (int i = 0; i < 4; i++) op[i * 256] = make_uint4(v[i][0], v[i][1], v[i][2], v[i][3]);
            if (blockIdx.x == 0 && tid == 128) asm volatile("st.relaxed.gpu.global.u32 [%0], %1;" :: "l"(&g_epoch), "r"(ep + 1) : "memory");
        }
        TS(15);
        TSDUMP();
    }
}

typedef CUresult (*EncFn)(CUtensorMap*, CUtensorMapDataType, cuuint32_t, void*, const cuuint64_t*, const cuuint64_t*, const cuuint32_t*,
                          const cuuint32_t*, CUtensorMapInterleave, CUtensorMapSwizzle, CUtensorMapL2promotion, CUtensorMapFloatOOBfill);

void encode(EncFn enc, CUtensorMap* tm, const void* base, int rank, cuuint64_t d0, cuuint64_t d1, cuuint64_t d2, cuuint64_t s1, cuuint64_t s2,
            cuuint32_t b0, cuuint32_t b1, cuuint32_t b2) {
    cuuint64_t gd[3] = {d0, d1, d2}, gs[2] = {s1, s2};
    cuuint32_t bd[3] = {b0, b1, b2}, es[3] = {1, 1, 1};
    enc(tm, CU_TENSOR_MAP_DATA_TYPE_BFLOAT16, rank, const_cast<void*>(base), gd, gs, bd, es, CU_TENSOR_MAP_INTERLEAVE_NONE,
        CU_TENSOR_MAP_SWIZZLE_128B, CU_TENSOR_MAP_L2_PROMOTION_L2_128B, CU_TENSOR_MAP_FLOAT_OOB_FILL_NONE);
}

}

extern "C" void kernel_launch(void* const* d_in, const int* in_sizes, int n_in, void* d_out, int out_size) {
    (void)in_sizes; (void)n_in; (void)out_size;
    static EncFn enc = nullptr;
    if (!enc) {
        void* fn = nullptr;
        cudaDriverEntryPointQueryResult qr;
        cudaGetDriverEntryPoint("cuTensorMapEncodeTiled", &fn, cudaEnableDefault, &qr);
        enc = (EncFn)fn;
        cudaFuncSetAttribute(fused_kernel, cudaFuncAttributeMaxDynamicSharedMemorySize, LAUNCH_SMEM);
    }
    Params P;
    encode(enc, &P.x, d_in[0], 3, 64, 2048, 8, 1024, 128, 64, 64, 2);
    encode(enc, &P.kv, d_in[1], 3, 512, 512, 3, 3072, 1024, 64, 64, 2);
    encode(enc, &P.q, d_in[1], 3, 512, 512, 3, 3072, 1024, 64, 64, 1);
    encode(enc, &P.w1a, d_in[5], 3, 1376, 512, 2, 2752, 128, 64, 64, 2);
    encode(enc, &P.w1b, d_in[5], 3, 1376, 512, 2, 2752, 128, 64, 64, 1);
    encode(enc, &P.w2h, d_in[7], 3, 64, 1376, 8, 1024, 128, 64, 88, 1);
    encode(enc, &P.woh, d_in[3], 3, 64, 512, 8, 1024, 128, 64, 64, 1);
    encode(enc, &P.w2, d_in[7], 3, 64, 1376, 8, 1024, 128, 64, 64, 2);
    encode(enc, &P.wo, d_in[3], 3, 64, 512, 8, 1024, 128, 64, 64, 2);
    encode(enc, &P.xr, d_in[0], 3, 64, 2048, 8, 1024, 128, 64, 128, 1);
    P.outp = d_out;
    P.xp = (const __nv_bfloat16*)d_in[0];
    P.wphi = (const __nv_bfloat16*)d_in[2];
    P.b1 = (const __nv_bfloat16*)d_in[6];
    P.b2 = (const __nv_bfloat16*)d_in[8];
    fused_kernel<<<128, 384, LAUNCH_SMEM, cudaStreamPerThread>>>(P);
}
```
